```python
import torch

def _softmax(x, axis=-1):
    return torch.softmax(x, dim=axis)

def _gelu(x):
    return torch.nn.functional.gelu(x, approximate='tanh')

def _silu(x):
    return torch.nn.functional.silu(x)

def _sigmoid(x):
    return torch.sigmoid(x)

def _layernorm(x, axis=-1, eps=1e-05):
    m = x.mean(dim=axis, keepdim=True)
    v = x.var(dim=axis, keepdim=True, unbiased=False)
    return (x - m) / torch.sqrt(v + eps)

def _scatter_add(tgt, idx, src, axis=0):
    return tgt.clone().index_add_(axis, idx, src)

def _segment_sum(src, seg, n):
    out = torch.zeros((n,) + src.shape[1:], dtype=src.dtype)
    return out.index_add_(0, seg, src)

def _pad(x, pw):
    flat = tuple((v for pair in reversed(pw) for v in pair))
    return torch.nn.functional.pad(x, flat)
kernel_name = 'concat_heads__mha_block__memory_aug_recurrent_mem_tr__prompt'

def setup_inputs():

    _w = lambda a: (lambda t: t.to(torch.bfloat16) if t.is_floating_point() else t)(torch.as_tensor(a))

    def _A_setup():
        B, S, D, H = (1, 2048, 512, 32)
        return {'x': _w((lambda *s: torch.randn(*s, dtype=torch.bfloat16) * 0.2)(B, S, D)), 'wqkv': _w((lambda *s: torch.randn(*s, dtype=torch.bfloat16) * 0.2)(D, 3 * D)), 'wo': _w((lambda *s: torch.randn(*s, dtype=torch.bfloat16) * 0.05)(D, D))}
    _A_in = _A_setup()

    def _B_setup():
        B, S, Dm = (1, 2048, 512)
        H, Dh = (32, 128)
        M, seg = (8, 32)
        seg = min(seg, S)
        S = S // seg * seg
        return {'x': _w((lambda *s: torch.randn(*s, dtype=torch.bfloat16) * 0.05)(B, S, Dm)), 'mem0': _w((lambda *s: torch.randn(*s, dtype=torch.bfloat16) * 0.8)(B, M, Dm)), 'Wq': _w((lambda *s: torch.randn(*s, dtype=torch.bfloat16) * 1.6)(Dm, H, Dh) * Dm ** (-0.5)), 'Wk': _w((lambda *s: torch.randn(*s, dtype=torch.bfloat16) * 1.6)(Dm, H, Dh) * Dm ** (-0.5)), 'Wv': _w((lambda *s: torch.randn(*s, dtype=torch.bfloat16) * 0.8)(Dm, H, Dh) * Dm ** (-0.5)), 'Wo': _w((lambda *s: torch.randn(*s, dtype=torch.bfloat16) * 0.8)(H, Dh, Dm) * (H * Dh) ** (-0.5)), 'seg_len': seg}
    _B_in = _B_setup()
    return {'A_x': _A_in['x'], 'A_wqkv': _A_in['wqkv'], 'A_wo': _A_in['wo'], 'B_x': _B_in['x'], 'B_mem0': _B_in['mem0'], 'B_Wq': _B_in['Wq'], 'B_Wk': _B_in['Wk'], 'B_Wv': _B_in['Wv'], 'B_Wo': _B_in['Wo'], 'B_seg_len': _B_in['seg_len']}

def reference(A_x, A_wqkv, A_wo, B_x, B_mem0, B_Wq, B_Wk, B_Wv, B_Wo, B_seg_len):

    def _A_ref(x, wqkv, wo):
        B, S, D = x.shape
        H = 32
        Dh = D // H
        qkv = (lambda x, *d: x.permute(*d))((x @ wqkv).reshape(B, S, 3, H, Dh), 2, 0, 3, 1, 4)
        q, k, v = (qkv[0], qkv[1], qkv[2])
        scores = torch.einsum('bhqd,bhkd->bhqk', q, k) * Dh ** (-0.5)
        p = _softmax(scores, axis=-1)
        o = torch.einsum('bhqk,bhkd->bhqd', p, v)
        return (lambda x, *d: x.permute(*d))(o, 0, 2, 1, 3).reshape(B, S, D) @ wo

    def _B_ref(x, mem0, Wq, Wk, Wv, Wo, seg_len):
        B, S, Dm = x.shape
        H, Dh = (Wq.shape[1], Wq.shape[2])
        M = mem0.shape[1]
        scale = Dh ** (-0.5)
        n_seg = S // seg_len
        L = M + seg_len
        idx = torch.arange(L)
        mask = (idx[:, None] < M) | (idx[:, None] >= idx[None, :])
        mem = mem0
        outs = []
        for s in range(n_seg):
            xs = x[:, s * seg_len:(s + 1) * seg_len, :].clone()
            h = torch.concatenate([mem, xs], axis=1)
            q = torch.einsum('btd,dhe->bhte', h, Wq)
            k = torch.einsum('btd,dhe->bhte', h, Wk)
            v = torch.einsum('btd,dhe->bhte', h, Wv)
            scores = torch.einsum('bhqe,bhke->bhqk', q, k) * scale
            scores = torch.where(mask[None, None], scores, -1000000000.0)
            p = _softmax(scores, axis=-1)
            o = torch.einsum('bhqk,bhke->bhqe', p, v)
            o = torch.einsum('bhte,hed->btd', o, Wo)
            mem = o[:, :M, :].clone()
            outs.append(o[:, M:, :])
        return torch.concatenate(outs, axis=1)
    a = _A_ref(A_x, A_wqkv, A_wo)
    b = _B_ref(B_x, B_mem0, B_Wq, B_Wk, B_Wv, B_Wo, B_seg_len)
    return torch.concatenate([a, b], axis=-1)
```

```cpp
#include <cuda_runtime.h>
#include <cuda_bf16.h>
#include <cuda.h>
#include <stdint.h>

typedef __nv_bfloat16 bf16;

constexpr int S_LEN = 2048;
constexpr int DM = 512;
constexpr int NH = 32;
constexpr int A_DH = 16;
constexpr int B_DH = 128;
constexpr int B_M = 8;
constexpr int SEG = 32;
constexpr int NSEG = 64;

__device__ float4 g_acc[NSEG][12][4][32];
__device__ unsigned g_gridbar;
__device__ bf16 g_otok[S_LEN * NH * B_DH];
__device__ uint4 g_tokqkv[NSEG * NH * 3 * 512];
__device__ uint32_t g_memkv[NSEG * NH * 2 * 512];
__device__ bf16 g_qkvA[3 * NH * S_LEN * A_DH];
__device__ bf16 g_oA[S_LEN * DM];

#define CH_MAXNREG __launch_bounds__(256, 1)
#define TSTAMP(i) do {} while (0)
__device__ __forceinline__ uint32_t smem_u32(const void* p) { return (uint32_t)__cvta_generic_to_shared(p); }
__device__ __forceinline__ uint32_t mapa(uint32_t a, uint32_t r) {
    uint32_t o; asm volatile("mapa.shared::cluster.u32 %0, %1, %2;" : "=r"(o) : "r"(a), "r"(r)); return o;
}
__device__ __forceinline__ void mbar_init(uint32_t a, uint32_t c) { asm volatile("mbarrier.init.shared.b64 [%0], %1;" :: "r"(a), "r"(c)); }
__device__ __forceinline__ void mbar_expect(uint32_t a, uint32_t b) {
    asm volatile("mbarrier.arrive.expect_tx.shared.b64 _, [%0], %1;" :: "r"(a), "r"(b) : "memory");
}
__device__ __forceinline__ void mbar_arrive(uint32_t a) {
    asm volatile("mbarrier.arrive.shared.b64 _, [%0];" :: "r"(a) : "memory");
}
__device__ __forceinline__ bool mbar_try(uint32_t a, uint32_t par) {
    uint32_t ok;
    asm volatile("{\n.reg .pred p;\nmbarrier.try_wait.parity.shared::cta.b64 p, [%1], %2;\nselp.u32 %0, 1, 0, p;\n}"
                 : "=r"(ok) : "r"(a), "r"(par) : "memory");
    return ok != 0;
}
__device__ __forceinline__ void mbar_wait(uint32_t a, uint32_t par) {
    #pragma unroll 1
    for (int it = 0; it < 4000000; it++) { if (mbar_try(a, par)) return; }
}
__device__ __forceinline__ void st_async_b32(uint32_t a, uint32_t x, uint32_t mb) {
    asm volatile("st.async.shared::cluster.mbarrier::complete_tx::bytes.b32 [%0], %1, [%2];" :: "r"(a), "r"(x), "r"(mb) : "memory");
}
__device__ __forceinline__ void st_async_v4(uint32_t a, uint32_t x, uint32_t y, uint32_t z, uint32_t w, uint32_t mb) {
    asm volatile("st.async.shared::cluster.mbarrier::complete_tx::bytes.v4.b32 [%0], {%1,%2,%3,%4}, [%5];"
                 :: "r"(a), "r"(x), "r"(y), "r"(z), "r"(w), "r"(mb) : "memory");
}
__device__ __forceinline__ void bulk_s2s(uint32_t dst, uint32_t src, uint32_t bytes, uint32_t mb) {
    asm volatile("cp.async.bulk.shared::cluster.shared::cta.mbarrier::complete_tx::bytes [%0], [%1], %2, [%3];"
                 :: "r"(dst), "r"(src), "r"(bytes), "r"(mb) : "memory");
}
__device__ __forceinline__ void cluster_sync() {
    asm volatile("barrier.cluster.arrive.aligned;\nbarrier.cluster.wait.aligned;" ::: "memory");
}
__device__ __forceinline__ float4 ld_relaxed_f4(const float4* p) {
    float4 v;
    asm volatile("ld.relaxed.gpu.global.v4.f32 {%0,%1,%2,%3}, [%4];" : "=f"(v.x), "=f"(v.y), "=f"(v.z), "=f"(v.w) : "l"(p) : "memory");
    return v;
}
__device__ __forceinline__ void red_v4(float4* p, float a, float b, float c, float d) {
    asm volatile("red.relaxed.gpu.global.add.v4.f32 [%0], {%1,%2,%3,%4};" :: "l"(p), "f"(a), "f"(b), "f"(c), "f"(d) : "memory");
}
__device__ __forceinline__ void ldsm4(uint32_t* r, uint32_t a) {
    asm volatile("ldmatrix.sync.aligned.m8n8.x4.shared.b16 {%0,%1,%2,%3}, [%4];"
                 : "=r"(r[0]), "=r"(r[1]), "=r"(r[2]), "=r"(r[3]) : "r"(a) : "memory");
}
__device__ __forceinline__ void ldsm4t(uint32_t* r, uint32_t a) {
    asm volatile("ldmatrix.sync.aligned.m8n8.x4.trans.shared.b16 {%0,%1,%2,%3}, [%4];"
                 : "=r"(r[0]), "=r"(r[1]), "=r"(r[2]), "=r"(r[3]) : "r"(a) : "memory");
}
__device__ __forceinline__ void ldsm2(uint32_t* r, uint32_t a) {
    asm volatile("ldmatrix.sync.aligned.m8n8.x2.shared.b16 {%0,%1}, [%2];"
                 : "=r"(r[0]), "=r"(r[1]) : "r"(a) : "memory");
}
__device__ __forceinline__ void mma16816(float* c, const uint32_t* a, uint32_t b0, uint32_t b1) {
    asm volatile("mma.sync.aligned.m16n8k16.row.col.f32.bf16.bf16.f32 {%0,%1,%2,%3}, {%4,%5,%6,%7}, {%8,%9}, {%0,%1,%2,%3};"
                 : "+f"(c[0]), "+f"(c[1]), "+f"(c[2]), "+f"(c[3])
                 : "r"(a[0]), "r"(a[1]), "r"(a[2]), "r"(a[3]), "r"(b0), "r"(b1));
}
__device__ __forceinline__ uint32_t pack_bf16(float lo, float hi) {
    uint32_t r; asm("cvt.rn.bf16x2.f32 %0, %1, %2;" : "=r"(r) : "f"(hi), "f"(lo)); return r;
}
__device__ __forceinline__ float ex2(float x) { float y; asm("ex2.approx.ftz.f32 %0, %1;" : "=f"(y) : "f"(x)); return y; }
__device__ __forceinline__ void cp_async16(uint32_t dst, const void* src) {
    asm volatile("cp.async.cg.shared.global [%0], [%1], 16;" :: "r"(dst), "l"(src) : "memory");
}
__device__ __forceinline__ void cp_async_wait_all() { asm volatile("cp.async.wait_all;" ::: "memory"); }
__device__ __forceinline__ void named_bar(int id, int n) { asm volatile("bar.sync %0, %1;" :: "r"(id), "r"(n) : "memory"); }
__device__ __forceinline__ uint64_t make_desc(uint32_t saddr, uint32_t lbo, uint32_t sbo, uint32_t swz) {
    uint64_t d = 0;
    d |= (uint64_t)((saddr & 0x3FFFF) >> 4);
    d |= (uint64_t)((lbo >> 4) & 0x3FFF) << 16;
    d |= (uint64_t)((sbo >> 4) & 0x3FFF) << 32;
    d |= (uint64_t)swz << 62;
    return d;
}
__device__ __forceinline__ void wg_fence() { asm volatile("wgmma.fence.sync.aligned;" ::: "memory"); }
__device__ __forceinline__ void wg_commit() { asm volatile("wgmma.commit_group.sync.aligned;" ::: "memory"); }
template <int N> __device__ __forceinline__ void wg_wait() { asm volatile("wgmma.wait_group.sync.aligned %0;" :: "n"(N) : "memory"); }
__device__ __forceinline__ void wgmma_rs_n32(float* d, const uint32_t* a, uint64_t desc, int scale_d) {
    asm volatile("{\n.reg .pred p;\nsetp.ne.b32 p, %21, 0;\n"
                 "wgmma.mma_async.sync.aligned.m64n32k16.f32.bf16.bf16 {%0,%1,%2,%3,%4,%5,%6,%7,%8,%9,%10,%11,%12,%13,%14,%15}, {%16,%17,%18,%19}, %20, p, 1, 1, 0;\n}"
                 : "+f"(d[0]), "+f"(d[1]), "+f"(d[2]), "+f"(d[3]), "+f"(d[4]), "+f"(d[5]), "+f"(d[6]), "+f"(d[7]),
                   "+f"(d[8]), "+f"(d[9]), "+f"(d[10]), "+f"(d[11]), "+f"(d[12]), "+f"(d[13]), "+f"(d[14]), "+f"(d[15])
                 : "r"(a[0]), "r"(a[1]), "r"(a[2]), "r"(a[3]), "l"(desc), "r"(scale_d));
}
__device__ __forceinline__ void tma_load_2d_mc(uint32_t dst, const CUtensorMap* tm, int c0, int c1, uint32_t mb, uint16_t mask) {
    asm volatile("cp.async.bulk.tensor.2d.shared::cluster.global.mbarrier::complete_tx::bytes.multicast::cluster [%0], [%1, {%3, %4}], [%2], %5;"
                 :: "r"(dst), "l"(tm), "r"(mb), "r"(c0), "r"(c1), "h"(mask) : "memory");
}
__device__ __forceinline__ void tma_load_2d(uint32_t dst, const CUtensorMap* tm, int c0, int c1, uint32_t mb) {
    asm volatile("cp.async.bulk.tensor.2d.shared::cluster.global.mbarrier::complete_tx::bytes [%0], [%1, {%3, %4}], [%2];"
                 :: "r"(dst), "l"(tm), "r"(mb), "r"(c0), "r"(c1) : "memory");
}

constexpr int CH_XS = 0;
constexpr int CH_KX = 65536;
constexpr int CH_VX = CH_KX + 30720;
constexpr int CH_MEMT = CH_VX + 30720;
constexpr int CH_KM = CH_MEMT + 8192;
constexpr int CH_VM = CH_KM + 2048;
constexpr int CH_QM = CH_VM + 2048;
constexpr int CH_SB = CH_QM + 2048;
constexpr int CH_OB = CH_SB + 1280;
constexpr int CH_BAR = CH_OB + 2048;
constexpr int CH_SMEM = CH_BAR + 128;
constexpr int CH_SMEM_ALLOC = 131072 + 128 * 400;
#define POLL_DELAY 1000
constexpr int TOKP = 80;
constexpr int WOP = 400;

template <int J0, int J1>
__device__ __forceinline__ void qkv_range(float (&c)[4][4], const uint32_t (&wr)[32][4], uint32_t memt_lane) {
    #pragma unroll
    for (int j = J0; j < J1; j++) {
        uint32_t b[4];
        ldsm4t(b, memt_lane + j * 512);
        mma16816(c[(2 * j) & 3], wr[2 * j], b[0], b[1]);
        mma16816(c[(2 * j + 1) & 3], wr[2 * j + 1], b[2], b[3]);
    }
}
__device__ __forceinline__ void bar_arrive(int id, int n) { asm volatile("bar.arrive %0, %1;" :: "r"(id), "r"(n) : "memory"); }

__global__ void __cluster_dims__(3, 1, 1) __launch_bounds__(384, 1)
chain_kernel(const __grid_constant__ CUtensorMap tmX, const bf16* __restrict__ mem0,
             const bf16* __restrict__ Wq, const bf16* __restrict__ Wk, const bf16* __restrict__ Wv,
             const bf16* __restrict__ Wo) {
    extern __shared__ __align__(1024) uint8_t smem[];
    const uint32_t sb = smem_u32(smem);
    uint32_t rank; asm volatile("mov.u32 %0, %%cluster_ctarank;" : "=r"(rank));
    const int tid = threadIdx.x, lane = tid & 31, warp = tid >> 5, wg = warp >> 2, w4 = warp & 3;
    const int g = lane >> 2, t = lane & 3;
    const int head = blockIdx.x / 3;
    const uint32_t barMem = sb + CH_BAR, barQK = barMem + 8, barV = barMem + 16, barTok = barMem + 24  , barX = barMem + 48  ;

    if (tid == 0) {
        mbar_init(barMem, 1); mbar_init(barQK, 1); mbar_init(barV, 1);
        mbar_init(barTok, 1); mbar_init(barTok + 8, 1); mbar_init(barTok + 16, 1); mbar_init(barX, 1); mbar_init(barX + 8, 1);
        asm volatile("fence.mbarrier_init.release.cluster;" ::: "memory");
    }
    {
        float4* p = &g_acc[0][0][0][0];
        constexpr int TOT = NSEG * 12 * 4 * 32;
        for (int i = blockIdx.x * 384 + tid; i < TOT; i += 96 * 384) p[i] = make_float4(0.f, 0.f, 0.f, 0.f);
    }
    const int tile0 = rank * 12 + w4 * 3;
    {
        const bf16* W = (rank == 0) ? Wq : (rank == 1 ? Wk : Wv);
        const int nf = (rank == 2) ? 128 : 192;
        for (int i = tid; i < 512 * 16; i += 384) {
            int d = i >> 4, c = i & 15;
            cp_async16(sb + (c >> 3) * 65536 + d * 128 + (((c & 7) ^ (d & 7)) << 4), W + (size_t)d * 4096 + head * 128 + c * 8);
        }
        for (int i = tid; i < 128 * (nf / 8); i += 384) {
            int e = i / (nf / 8), c = i % (nf / 8);
            cp_async16(sb + 131072 + e * WOP + c * 16, Wo + (size_t)(head * 128 + e) * 512 + rank * 192 + c * 8);
        }
        cp_async_wait_all();
        __threadfence();
        __syncthreads();
    }
    const uint32_t pr0 = mapa(sb, rank == 0 ? 1 : 0), pr1 = mapa(sb, rank == 2 ? 1 : 2);
    const uint32_t self = mapa(sb, rank);
    const int mi = lane >> 3, r8 = lane & 7;

    if (wg == 2) {
        asm volatile("setmaxnreg.dec.sync.aligned.u32 136;");
        uint32_t wr[24][4];
        #pragma unroll
        for (int i = 0; i < 3; i++)
            #pragma unroll
            for (int kk = 0; kk < 8; kk++) {
                if (tile0 + i < 32) ldsm4t(wr[i * 8 + kk], sb + 131072 + (kk * 16 + (mi >> 1) * 8 + r8) * WOP + ((w4 * 3 + i) * 16 + (mi & 1) * 8) * 2);
                else { wr[i * 8 + kk][0] = 0; wr[i * 8 + kk][1] = 0; wr[i * 8 + kk][2] = 0; wr[i * 8 + kk][3] = 0; }
            }
        unsigned bar_target = 0;
        if (tid == 256) {
            unsigned ticket = atomicAdd(&g_gridbar, 1u);
            bar_target = (ticket / 96u + 1u) * 96u;
        }
        cluster_sync();
        const bool boss = (tid == 256 + 96);
        const uint32_t mem_remote_bytes = 8192 - ((rank == 2) ? 2048 : 3072);
        const uint32_t tok_bytes = (rank == 0) ? 20480 : 10240;
        const int nvalid = min(max(32 - tile0, 0), 3);
        const int slot = rank * 4 + w4;
        auto issue_x = [&](int seg) {
            mbar_expect(barX + (seg & 1) * 8, 32768);
            #pragma unroll 1
            for (int c = rank; c < 8; c += 3)
                tma_load_2d_mc(sb + CH_XS + (seg & 1) * 32768 + c * 4096, &tmX, c * 64, seg * SEG, barX + (seg & 1) * 8, (uint16_t)7);
        };
        if (boss) {
            mbar_expect(barTok, tok_bytes); mbar_expect(barTok + 8, tok_bytes); mbar_expect(barTok + 16, tok_bytes);
            issue_x(0); issue_x(1);
        }
        long long t_red = clock64();
        #pragma unroll 1
        for (int s = 0; s < NSEG; s++) {
            const int par = s & 1;
            const int tb = s % 3, tph = (s / 3) & 1;
            TSTAMP(0);
            if (boss) { mbar_expect(barMem, mem_remote_bytes); mbar_expect(barQK, 4096); mbar_expect(barV, 2048); }
            if (nvalid > 0) {
                float v[12];
                if (s == 0) {
                    #pragma unroll
                    for (int i = 0; i < 3; i++)
                        #pragma unroll
                        for (int hf = 0; hf < 2; hf++) {
                            int f = min((tile0 + i) * 16 + hf * 8 + g, 511);
                            v[i * 4 + hf * 2] = __bfloat162float(mem0[(2 * t) * 512 + f]);
                            v[i * 4 + hf * 2 + 1] = __bfloat162float(mem0[(2 * t + 1) * 512 + f]);
                        }
                } else {
                    const float4* src = &g_acc[s][slot][0][lane];
                    while (clock64() - t_red < POLL_DELAY) {}
                    float4 a, b, c, d;
                    d = make_float4(0.f, 0.f, 0.f, 32.f);
                    #pragma unroll 1
                    for (int it = 0; it < 2000000; it++) {
                        a = ld_relaxed_f4(src); b = ld_relaxed_f4(src + 32); c = ld_relaxed_f4(src + 64);
                        if (nvalid == 3) d = ld_relaxed_f4(src + 96);
                        if (a.w == 32.f && b.w == 32.f && c.w == 32.f && d.w == 32.f) break;
                    }
                    v[0] = a.x; v[1] = a.y; v[2] = a.z; v[3] = b.x; v[4] = b.y; v[5] = b.z;
                    v[6] = c.x; v[7] = c.y; v[8] = c.z; v[9] = d.x; v[10] = d.y; v[11] = d.z;
                }
                TSTAMP(1);
                const uint32_t off0 = CH_MEMT + (tile0 * 16 + g) * 16 + t * 4;
                uint32_t wv[6];
                #pragma unroll
                for (int q = 0; q < 6; q++) wv[q] = pack_bf16(v[2 * q], v[2 * q + 1]);
                #pragma unroll
                for (int q = 0; q < 6; q++) if (q < 4 || nvalid == 3) st_async_b32(pr0 + off0 + q * 128, wv[q], pr0 + CH_BAR);
                #pragma unroll
                for (int q = 0; q < 6; q++) if (q < 4 || nvalid == 3) st_async_b32(pr1 + off0 + q * 128, wv[q], pr1 + CH_BAR);
                #pragma unroll
                for (int q = 0; q < 6; q++) if (q < 4 || nvalid == 3) asm volatile("st.shared.b32 [%0], %1;" :: "r"(sb + off0 + q * 128), "r"(wv[q]) : "memory");
            }
            bar_arrive(1, 384);
            if (boss) {
                mbar_wait(barQK, par); mbar_wait(barV, par);
                if (s == 0) issue_x(2);
                if (s + 3 < NSEG) { issue_x(s + 3); }
                mbar_wait(barTok + tb * 8, tph);
                if (s + 3 < NSEG) mbar_expect(barTok + tb * 8, tok_bytes);
            }
            __syncwarp();
            if (s + 1 < NSEG) {
                named_bar(3, 384);
                TSTAMP(6);
                if (nvalid > 0) {
                    float c[6][4] = {};
                    #pragma unroll
                    for (int kk = 0; kk < 8; kk++) {
                        uint2 ob = *(const uint2*)(smem + CH_OB + kk * 256 + lane * 8);
                        #pragma unroll
                        for (int i = 0; i < 3; i++) mma16816(c[i * 2 + (kk & 1)], wr[i * 8 + kk], ob.x, ob.y);
                    }
                    if (s == 0) {
                        if (tid == 256) {
                            for (int it = 0; it < 2000000; it++) {
                                unsigned v; asm volatile("ld.acquire.gpu.global.u32 %0, [%1];" : "=r"(v) : "l"(&g_gridbar) : "memory");
                                if ((int)(v - bar_target) >= 0) break;
                            }
                        }
                    }
                    TSTAMP(13);
                    float o[12];
                    #pragma unroll
                    for (int i = 0; i < 3; i++)
                        #pragma unroll
                        for (int e = 0; e < 4; e++) o[i * 4 + e] = c[2 * i][e] + c[2 * i + 1][e];
                    bar_arrive(6, 384);
                    if (s == 0) named_bar(5, (rank == 2) ? 96 : 128);
                    float4* dst = &g_acc[s + 1][slot][0][lane];
                    red_v4(dst, o[0], o[1], o[2], 1.f);
                    red_v4(dst + 32, o[3], o[4], o[5], 1.f);
                    red_v4(dst + 64, o[6], o[7], o[8], 1.f);
                    if (nvalid == 3) red_v4(dst + 96, o[9], o[10], o[11], 1.f);
                } else {
                    bar_arrive(6, 384);
                }
                t_red = clock64();
                TSTAMP(7);
            }
        }
    } else {
        asm volatile("setmaxnreg.inc.sync.aligned.u32 184;");
        uint32_t wr[32][4];
        #pragma unroll
        for (int kk = 0; kk < 32; kk++) {
            int d = kk * 16 + (mi >> 1) * 8 + r8;
            int c = w4 * 2 + (mi & 1);
            ldsm4t(wr[kk], sb + wg * 65536 + d * 128 + ((c ^ (d & 7)) << 4));
        }
        cluster_sync();
        float xacc[16];
        auto xproj = [&](int seg) {
            mbar_wait(barX + (seg & 1) * 8, (seg >> 1) & 1);
            wg_fence();
            #pragma unroll
            for (int kk = 0; kk < 32; kk++) {
                uint64_t desc = make_desc(sb + CH_XS + (seg & 1) * 32768 + (kk >> 2) * 4096 + (kk & 3) * 32, 16, 1024, 1);
                wgmma_rs_n32(xacc, wr[kk], desc, kk > 0);
            }
            wg_commit();
            wg_wait<0>();
            const int buf = seg % 3;
            uint32_t p0[4], p1[4];
            #pragma unroll
            for (int j = 0; j < 4; j++) { p0[j] = pack_bf16(xacc[4 * j], xacc[4 * j + 1]); p1[j] = pack_bf16(xacc[4 * j + 2], xacc[4 * j + 3]); }
            const int e = wg * 64 + w4 * 16 + g;
            if (rank != 0) {
                const uint32_t boff = ((rank == 1) ? CH_KX : CH_VX) + buf * 10240;
                const uint32_t a = sb + boff + e * TOKP + t * 16;
                asm volatile("st.shared.v4.b32 [%0], {%1,%2,%3,%4};" :: "r"(a), "r"(p0[0]), "r"(p0[1]), "r"(p0[2]), "r"(p0[3]) : "memory");
                asm volatile("st.shared.v4.b32 [%0], {%1,%2,%3,%4};" :: "r"(a + 8 * TOKP), "r"(p1[0]), "r"(p1[1]), "r"(p1[2]), "r"(p1[3]) : "memory");
                asm volatile("fence.proxy.async.shared::cta;" ::: "memory");
            }
            uint4* gp = g_tokqkv + (size_t)((seg * NH + head) * 3 + rank) * 512 + e * 4 + (t ^ ((e >> 1) & 3));
            gp[0] = make_uint4(p0[0], p0[1], p0[2], p0[3]);
            gp[32] = make_uint4(p1[0], p1[1], p1[2], p1[3]);
        };
        auto tok_bcast = [&](int seg) {
            if (rank != 0 && tid == 224) {
                const int buf = seg % 3;
                const uint32_t boff = ((rank == 1) ? CH_KX : CH_VX) + buf * 10240;
                bulk_s2s(pr0 + boff, sb + boff, 10240, pr0 + CH_BAR + 24 + buf * 8);
                bulk_s2s(pr1 + boff, sb + boff, 10240, pr1 + CH_BAR + 24 + buf * 8);
            }
        };
        xproj(0);
        xproj(1);
        named_bar(4, 256);
        tok_bcast(0);
        const float sc2 = 0.08838834764831845f * 1.4426950408889634f;
        const uint32_t memt_lane = sb + CH_MEMT + lane * 16;

        #pragma unroll 1
        for (int s = 0; s < NSEG; s++) {
            const int par = s & 1;
            const int tb = s % 3, tph = (s / 3) & 1;
            TSTAMP(0);
            named_bar(1, 384);
            TSTAMP(1);
            {
                float c[4][4] = {};
                if (rank == 0) {
                    qkv_range<0, 6>(c, wr, memt_lane);
                    mbar_wait(barMem, par); TSTAMP(2);
                    qkv_range<6, 16>(c, wr, memt_lane);
                } else if (rank == 1) {
                    qkv_range<6, 12>(c, wr, memt_lane);
                    mbar_wait(barMem, par); TSTAMP(2);
                    qkv_range<0, 6>(c, wr, memt_lane);
                    qkv_range<12, 16>(c, wr, memt_lane);
                } else {
                    qkv_range<12, 16>(c, wr, memt_lane);
                    mbar_wait(barMem, par); TSTAMP(2);
                    qkv_range<0, 12>(c, wr, memt_lane);
                }
                float r0 = (c[0][0] + c[1][0]) + (c[2][0] + c[3][0]);
                float r1 = (c[0][1] + c[1][1]) + (c[2][1] + c[3][1]);
                float r2 = (c[0][2] + c[1][2]) + (c[2][2] + c[3][2]);
                float r3 = (c[0][3] + c[1][3]) + (c[2][3] + c[3][3]);
                uint32_t w0 = pack_bf16(r0, r1), w1 = pack_bf16(r2, r3);
                TSTAMP(10);
                const int e = wg * 64 + w4 * 16 + g;
                uint32_t off = (rank == 0 ? CH_QM : (rank == 1 ? CH_KM : CH_VM)) + e * 16 + t * 4;
                uint32_t boff = CH_BAR + (rank == 2 ? 16 : 8);
                st_async_b32(pr0 + off, w0, pr0 + boff);
                st_async_b32(pr0 + off + 128, w1, pr0 + boff);
                st_async_b32(pr1 + off, w0, pr1 + boff);
                st_async_b32(pr1 + off + 128, w1, pr1 + boff);
                st_async_b32(self + off, w0, self + boff);
                st_async_b32(self + off + 128, w1, self + boff);
                if (rank != 0) {
                    uint32_t* gp = g_memkv + (size_t)((s * NH + head) * 2 + (rank - 1)) * 512 + e * 4 + t;
                    gp[0] = w0; gp[32] = w1;
                }
            }
            TSTAMP(3);
            mbar_wait(barTok + tb * 8, tph);
            uint32_t kb[4][4];
            if (warp >= 1 && warp < 5) {
                #pragma unroll
                for (int j = 0; j < 4; j++)
                    ldsm4t(kb[j], sb + CH_KX + tb * 10240 + (j * 32 + lane) * TOKP + (warp - 1) * 16);
            }
            uint32_t vx[2][4], vm[2];
            #pragma unroll
            for (int nt = 0; nt < 2; nt++)
                ldsm4(vx[nt], sb + CH_VX + tb * 10240 + (warp * 16 + nt * 8 + (lane & 7)) * TOKP + (lane >> 3) * 16);
            mbar_wait(barQK, par);
            TSTAMP(4);
            if (warp < 5) {
                if (warp == 0) {
                    #pragma unroll
                    for (int j = 0; j < 4; j++) ldsm4t(kb[j], sb + CH_KM + (j * 32 + lane) * 16);
                }
                float c[4][4] = {};
                #pragma unroll
                for (int j = 0; j < 4; j++) {
                    uint32_t q[4];
                    ldsm4t(q, sb + CH_QM + (j * 32 + lane) * 16);
                    uint32_t a0[4] = { q[0], 0u, q[1], 0u };
                    uint32_t a1[4] = { q[2], 0u, q[3], 0u };
                    mma16816(c[(2 * j) & 3], a0, kb[j][0], kb[j][1]);
                    mma16816(c[(2 * j + 1) & 3], a1, kb[j][2], kb[j][3]);
                }
                float2 sv = make_float2((c[0][0] + c[1][0]) + (c[2][0] + c[3][0]), (c[0][1] + c[1][1]) + (c[2][1] + c[3][1]));
                *(float2*)(smem + CH_SB + warp * 256 + lane * 8) = sv;
            }
            mbar_wait(barV, par);
            ldsm2(vm, sb + CH_VM + (warp * 16 + (lane & 15)) * 16);
            named_bar(2, 256);
            if (s + 1 < NSEG) tok_bcast(s + 1);
            TSTAMP(5);
            {
                float sv[10];
                #pragma unroll
                for (int i = 0; i < 5; i++) {
                    float2 x = *(const float2*)(smem + CH_SB + i * 256 + lane * 8);
                    sv[2 * i] = x.x; sv[2 * i + 1] = x.y;
                }
                float m = fmaxf(fmaxf(fmaxf(sv[0], sv[1]), fmaxf(sv[2], sv[3])), fmaxf(fmaxf(sv[4], sv[5]), fmaxf(sv[6], sv[7])));
                m = fmaxf(m, fmaxf(sv[8], sv[9]));
                m = fmaxf(m, __shfl_xor_sync(~0u, m, 1));
                m = fmaxf(m, __shfl_xor_sync(~0u, m, 2));
                const float ms = -m * sc2;
                #pragma unroll
                for (int i = 0; i < 10; i++) sv[i] = ex2(fmaf(sv[i], sc2, ms));
                uint32_t pa[3][4];
                pa[0][0] = pack_bf16(sv[0], sv[1]); pa[0][1] = 0; pa[0][2] = pack_bf16(sv[2], sv[3]); pa[0][3] = 0;
                pa[1][0] = pack_bf16(sv[4], sv[5]); pa[1][1] = 0; pa[1][2] = pack_bf16(sv[6], sv[7]); pa[1][3] = 0;
                pa[2][0] = pack_bf16(sv[8], sv[9]); pa[2][1] = 0; pa[2][2] = 0; pa[2][3] = 0;
                TSTAMP(11);
                float c0[2][4] = {}, c1[2][4] = {};
                #pragma unroll
                for (int nt = 0; nt < 2; nt++) {
                    mma16816(c0[nt], pa[0], vm[nt], vx[nt][0]);
                    mma16816(c1[nt], pa[1], vx[nt][1], vx[nt][2]);
                }
                #pragma unroll
                for (int nt = 0; nt < 2; nt++) mma16816(c0[nt], pa[2], vx[nt][3], 0u);
                float l = ((sv[0] + sv[1]) + (sv[2] + sv[3])) + ((sv[4] + sv[5]) + (sv[6] + sv[7])) + (sv[8] + sv[9]);
                l += __shfl_xor_sync(~0u, l, 1);
                l += __shfl_xor_sync(~0u, l, 2);
                const float inv_l = __frcp_rn(l);
                uint32_t ow0 = pack_bf16((c0[0][0] + c1[0][0]) * inv_l, (c0[0][1] + c1[0][1]) * inv_l);
                uint32_t ow1 = pack_bf16((c0[1][0] + c1[1][0]) * inv_l, (c0[1][1] + c1[1][1]) * inv_l);
                *(uint2*)(smem + CH_OB + warp * 256 + lane * 8) = make_uint2(ow0, ow1);
            }
            if (s + 1 < NSEG) {
                bar_arrive(3, 384);
                named_bar(6, 384);
                TSTAMP(8);
                if (s + 2 < NSEG) xproj(s + 2);
            }
            TSTAMP(9);
        }
    }
    __syncthreads();
    cluster_sync();
}

constexpr int TK_BUF = 24576 + 4096;
__device__ __forceinline__ void bulk_g2s(uint32_t dst, const void* src, uint32_t bytes, uint32_t mb) {
    asm volatile("cp.async.bulk.shared::cluster.global.mbarrier::complete_tx::bytes [%0], [%1], %2, [%3];"
                 :: "r"(dst), "l"(src), "r"(bytes), "r"(mb) : "memory");
}
__global__ void __launch_bounds__(128) tokattn_kernel(int tile0, int ntiles) {
    extern __shared__ __align__(128) uint8_t sm[];
    const int tid = threadIdx.x, lane = tid & 31, warp = tid >> 5;
    const int g = lane >> 2, t = lane & 3;
    const uint32_t sb = smem_u32(sm), bar = sb + 2 * TK_BUF;
    if (tid == 0) { mbar_init(bar, 1); mbar_init(bar + 8, 1); asm volatile("fence.mbarrier_init.release.cluster;" ::: "memory"); }
    __syncthreads();
    auto prefetch = [&](int tile, int b) {
        if (tid == 0) {
            mbar_expect(bar + b * 8, TK_BUF);
            bulk_g2s(sb + b * TK_BUF, g_tokqkv + (size_t)tile * 3 * 512, 24576, bar + b * 8);
            bulk_g2s(sb + b * TK_BUF + 24576, g_memkv + (size_t)tile * 2 * 512, 4096, bar + b * 8);
        }
    };
    const float sc2 = 0.08838834764831845f * 1.4426950408889634f;
    const int mt = warp & 1, dh = warp >> 1;
    const int mi = lane >> 3, r8 = lane & 7;
    int it = 0;
    int tile = tile0 + blockIdx.x;
    const int tend = tile0 + ntiles;
    if (tile < tend) prefetch(tile, 0);
    for (; tile < tend; tile += gridDim.x, it++) {
        const int b = it & 1;
        if (tile + (int)gridDim.x < tend) prefetch(tile + gridDim.x, b ^ 1);
        mbar_wait(bar + b * 8, (it >> 1) & 1);
        const int seg = tile >> 5, head = tile & 31;
        const uint32_t sQ = sb + b * TK_BUF, sK = sQ + 8192, sV = sQ + 16384, sKM = sQ + 24576, sVM = sQ + 26624;
        float sc[5][4] = {};
        #pragma unroll
        for (int j = 0; j < 4; j++) {
            uint32_t qa[2][4];
            #pragma unroll
            for (int h2 = 0; h2 < 2; h2++) {
                const int dim = j * 32 + h2 * 16 + (mi >> 1) * 8 + r8;
                ldsm4t(qa[h2], sQ + dim * 64 + (((mt * 2 + (mi & 1)) ^ ((dim >> 1) & 3)) << 4));
            }
            uint32_t bb[4];
            ldsm4t(bb, sKM + (j * 32 + lane) * 16);
            mma16816(sc[0], qa[0], bb[0], bb[1]);
            mma16816(sc[0], qa[1], bb[2], bb[3]);
            #pragma unroll
            for (int i = 1; i < 5; i++) {
                const int dim = j * 32 + lane;
                ldsm4t(bb, sK + dim * 64 + (((i - 1) ^ ((dim >> 1) & 3)) << 4));
                mma16816(sc[i], qa[0], bb[0], bb[1]);
                mma16816(sc[i], qa[1], bb[2], bb[3]);
            }
        }
        const int tq0 = 8 * (g >> 1) + 2 * (2 * mt) + (g & 1);
        const int tq1 = tq0 + 2;
        float m0 = fmaxf(sc[0][0], sc[0][1]), m1 = fmaxf(sc[0][2], sc[0][3]);
        #pragma unroll
        for (int i = 1; i < 5; i++) {
            #pragma unroll
            for (int e2 = 0; e2 < 2; e2++) {
                int tk = 8 * t + 2 * (i - 1) + e2;
                if (tk > tq0) sc[i][e2] = -INFINITY;
                if (tk > tq1) sc[i][2 + e2] = -INFINITY;
                m0 = fmaxf(m0, sc[i][e2]); m1 = fmaxf(m1, sc[i][2 + e2]);
            }
        }
        m0 = fmaxf(m0, __shfl_xor_sync(~0u, m0, 1)); m0 = fmaxf(m0, __shfl_xor_sync(~0u, m0, 2));
        m1 = fmaxf(m1, __shfl_xor_sync(~0u, m1, 1)); m1 = fmaxf(m1, __shfl_xor_sync(~0u, m1, 2));
        float l0 = 0.f, l1 = 0.f;
        #pragma unroll
        for (int i = 0; i < 5; i++) {
            sc[i][0] = ex2((sc[i][0] - m0) * sc2); sc[i][1] = ex2((sc[i][1] - m0) * sc2);
            sc[i][2] = ex2((sc[i][2] - m1) * sc2); sc[i][3] = ex2((sc[i][3] - m1) * sc2);
            l0 += sc[i][0] + sc[i][1]; l1 += sc[i][2] + sc[i][3];
        }
        l0 += __shfl_xor_sync(~0u, l0, 1); l0 += __shfl_xor_sync(~0u, l0, 2);
        l1 += __shfl_xor_sync(~0u, l1, 1); l1 += __shfl_xor_sync(~0u, l1, 2);
        const float i0 = 1.f / l0, i1 = 1.f / l1;
        uint32_t pp[3][4];
        pp[0][0] = pack_bf16(sc[0][0], sc[0][1]); pp[0][1] = pack_bf16(sc[0][2], sc[0][3]);
        pp[0][2] = pack_bf16(sc[1][0], sc[1][1]); pp[0][3] = pack_bf16(sc[1][2], sc[1][3]);
        pp[1][0] = pack_bf16(sc[2][0], sc[2][1]); pp[1][1] = pack_bf16(sc[2][2], sc[2][3]);
        pp[1][2] = pack_bf16(sc[3][0], sc[3][1]); pp[1][3] = pack_bf16(sc[3][2], sc[3][3]);
        pp[2][0] = pack_bf16(sc[4][0], sc[4][1]); pp[2][1] = pack_bf16(sc[4][2], sc[4][3]);
        pp[2][2] = 0; pp[2][3] = 0;
        bf16* o0p = g_otok + (size_t)(seg * SEG + tq0) * 4096 + head * 128 + dh * 64 + 2 * t;
        bf16* o1p = o0p + 2 * 4096;
        #pragma unroll
        for (int nt = 0; nt < 8; nt++) {
            uint32_t vx[4], vm[2];
            const int dim = dh * 64 + nt * 8 + r8;
            ldsm4(vx, sV + dim * 64 + ((mi ^ ((dim >> 1) & 3)) << 4));
            ldsm2(vm, sVM + dim * 16);
            float c[4] = {};
            mma16816(c, pp[0], vm[0], vx[0]);
            mma16816(c, pp[1], vx[1], vx[2]);
            mma16816(c, pp[2], vx[3], 0u);
            *(uint32_t*)(o0p + nt * 8) = pack_bf16(c[0] * i0, c[1] * i0);
            *(uint32_t*)(o1p + nt * 8) = pack_bf16(c[2] * i1, c[3] * i1);
        }
        __syncthreads();
    }
}

constexpr int GM_STAGES = 4;
constexpr int GM_STAGE_BYTES = 32768;
constexpr int GM_SMEM = GM_STAGES * GM_STAGE_BYTES + 1024;

__device__ __forceinline__ void wgmma_ss_n128_tb(float* d, uint64_t da, uint64_t db, int scale_d) {
    asm volatile("{\n.reg .pred p;\nsetp.ne.b32 p, %66, 0;\n"
        "wgmma.mma_async.sync.aligned.m64n128k16.f32.bf16.bf16 "
        "{%0,%1,%2,%3,%4,%5,%6,%7,%8,%9,%10,%11,%12,%13,%14,%15,%16,%17,%18,%19,%20,%21,%22,%23,%24,%25,%26,%27,%28,%29,%30,%31,"
        "%32,%33,%34,%35,%36,%37,%38,%39,%40,%41,%42,%43,%44,%45,%46,%47,%48,%49,%50,%51,%52,%53,%54,%55,%56,%57,%58,%59,%60,%61,%62,%63}, "
        "%64, %65, p, 1, 1, 0, 1;\n}"
        : "+f"(d[0]), "+f"(d[1]), "+f"(d[2]), "+f"(d[3]), "+f"(d[4]), "+f"(d[5]), "+f"(d[6]), "+f"(d[7]),
          "+f"(d[8]), "+f"(d[9]), "+f"(d[10]), "+f"(d[11]), "+f"(d[12]), "+f"(d[13]), "+f"(d[14]), "+f"(d[15]),
          "+f"(d[16]), "+f"(d[17]), "+f"(d[18]), "+f"(d[19]), "+f"(d[20]), "+f"(d[21]), "+f"(d[22]), "+f"(d[23]),
          "+f"(d[24]), "+f"(d[25]), "+f"(d[26]), "+f"(d[27]), "+f"(d[28]), "+f"(d[29]), "+f"(d[30]), "+f"(d[31]),
          "+f"(d[32]), "+f"(d[33]), "+f"(d[34]), "+f"(d[35]), "+f"(d[36]), "+f"(d[37]), "+f"(d[38]), "+f"(d[39]),
          "+f"(d[40]), "+f"(d[41]), "+f"(d[42]), "+f"(d[43]), "+f"(d[44]), "+f"(d[45]), "+f"(d[46]), "+f"(d[47]),
          "+f"(d[48]), "+f"(d[49]), "+f"(d[50]), "+f"(d[51]), "+f"(d[52]), "+f"(d[53]), "+f"(d[54]), "+f"(d[55]),
          "+f"(d[56]), "+f"(d[57]), "+f"(d[58]), "+f"(d[59]), "+f"(d[60]), "+f"(d[61]), "+f"(d[62]), "+f"(d[63])
        : "l"(da), "l"(db), "r"(scale_d));
}

template <int MODE, int KSPLIT>
__global__ void __launch_bounds__(288, 1)
gemm_tma(const __grid_constant__ CUtensorMap tmA, const __grid_constant__ CUtensorMap tmB, bf16* __restrict__ C,
         int K, int ntn, int ldc, int coff) {
    extern __shared__ __align__(1024) uint8_t smem_raw[];
    const uint32_t sb = (smem_u32(smem_raw) + 1023) & ~1023u;
    const uint32_t bar0 = sb + GM_STAGES * GM_STAGE_BYTES;
    const int tid = threadIdx.x, lane = tid & 31, warp = tid >> 5;
    const int ks = (KSPLIT == 2) ? (blockIdx.x & 1) : 0;
    const int tile = blockIdx.x / KSPLIT;
    const int m0 = (tile / ntn) * 128, n0 = (tile % ntn) * 128;
    const int kper = K / KSPLIT, kbase = ks * kper, nk = kper / 64;
    if (tid == 0) {
        for (int i = 0; i < GM_STAGES; i++) { mbar_init(bar0 + i * 8, 1); mbar_init(bar0 + 32 + i * 8, 2); }
        asm volatile("fence.mbarrier_init.release.cluster;" ::: "memory");
    }
    __syncthreads();
    if (warp == 8) {
        if (lane == 0) {
            for (int it = 0; it < nk; it++) {
                const int st = it % GM_STAGES, ph = (it / GM_STAGES) & 1;
                mbar_wait(bar0 + 32 + st * 8, ph ^ 1);
                mbar_expect(bar0 + st * 8, GM_STAGE_BYTES);
                const uint32_t sA = sb + st * GM_STAGE_BYTES, sB = sA + 16384;
                const int k0 = kbase + it * 64;
                tma_load_2d(sA, &tmA, k0, m0, bar0 + st * 8);
                tma_load_2d(sB, &tmB, n0, k0, bar0 + st * 8);
                tma_load_2d(sB + 8192, &tmB, n0 + 64, k0, bar0 + st * 8);
            }
        }
    } else {
        const int wg = warp >> 2, w4 = warp & 3, g = lane >> 2, t = lane & 3;
        float acc[64];
        for (int it = 0; it < nk; it++) {
            const int st = it % GM_STAGES, ph = (it / GM_STAGES) & 1;
            mbar_wait(bar0 + st * 8, ph);
            const uint32_t sA = sb + st * GM_STAGE_BYTES + wg * 8192, sB = sb + st * GM_STAGE_BYTES + 16384;
            wg_fence();
            #pragma unroll
            for (int kk = 0; kk < 4; kk++) {
                uint64_t da = make_desc(sA + kk * 32, 16, 1024, 1);
                uint64_t db = make_desc(sB + kk * 2048, 8192, 1024, 1);
                wgmma_ss_n128_tb(acc, da, db, (it > 0 || kk > 0));
            }
            wg_commit();
            if (it > 0) {
                wg_wait<1>();
                if ((tid & 127) == 0) mbar_arrive(bar0 + 32 + ((it - 1) % GM_STAGES) * 8);
            }
        }
        wg_wait<0>();
        #pragma unroll
        for (int j = 0; j < 64; j++) asm volatile("" : "+f"(acc[j]) :: "memory");
        if (KSPLIT == 2) {
            named_bar(1, 256);
            asm volatile("barrier.cluster.arrive.aligned;\nbarrier.cluster.wait.aligned;" ::: "memory");
            const uint32_t red = mapa(sb, 0) + tid * 16;
            if (ks == 1) {
                #pragma unroll
                for (int j = 0; j < 16; j++)
                    asm volatile("st.shared::cluster.v4.f32 [%0], {%1,%2,%3,%4};" :: "r"(red + j * 4096), "f"(acc[4 * j]), "f"(acc[4 * j + 1]), "f"(acc[4 * j + 2]), "f"(acc[4 * j + 3]) : "memory");
            }
            asm volatile("barrier.cluster.arrive.aligned;\nbarrier.cluster.wait.aligned;" ::: "memory");
            if (ks == 1) return;
            #pragma unroll
            for (int j = 0; j < 16; j++) {
                float4 v;
                asm volatile("ld.shared.v4.f32 {%0,%1,%2,%3}, [%4];" : "=f"(v.x), "=f"(v.y), "=f"(v.z), "=f"(v.w) : "r"(sb + tid * 16 + j * 4096) : "memory");
                acc[4 * j] += v.x; acc[4 * j + 1] += v.y; acc[4 * j + 2] += v.z; acc[4 * j + 3] += v.w;
            }
        }
        const int row0 = m0 + wg * 64 + w4 * 16 + g;
        #pragma unroll
        for (int j = 0; j < 16; j++) {
            const int col = n0 + j * 8 + 2 * t;
            #pragma unroll
            for (int hh = 0; hh < 2; hh++) {
                const int row = row0 + hh * 8;
                const uint32_t v = pack_bf16(acc[4 * j + 2 * hh], acc[4 * j + 2 * hh + 1]);
                if (MODE == 0) {
                    const int which = col >> 9, h = (col >> 4) & 31, d = col & 15;
                    *(uint32_t*)(C + ((size_t)(which * NH + h) * S_LEN + row) * 16 + d) = v;
                } else {
                    *(uint32_t*)(C + (size_t)row * ldc + coff + col) = v;
                }
            }
        }
    }
    if (KSPLIT == 2 && warp == 8) {
        asm volatile("barrier.cluster.arrive.aligned;\nbarrier.cluster.wait.aligned;" ::: "memory");
        asm volatile("barrier.cluster.arrive.aligned;\nbarrier.cluster.wait.aligned;" ::: "memory");
    }
}

__device__ float g_kmax2[NH];

__global__ void __launch_bounds__(256) knorm_kernel(const bf16* __restrict__ qkv) {
    const int h = blockIdx.x, tid = threadIdx.x;
    const uint4* Kp = (const uint4*)(qkv + (size_t)(1 * NH + h) * S_LEN * 16);
    float mx = 0.f;
    for (int j = tid; j < S_LEN; j += 256) {
        uint4 a = Kp[2 * j], b = Kp[2 * j + 1];
        const uint32_t w[8] = { a.x, a.y, a.z, a.w, b.x, b.y, b.z, b.w };
        float s = 0.f;
        #pragma unroll
        for (int i = 0; i < 8; i++) {
            float lo = __uint_as_float(w[i] << 16), hi = __uint_as_float(w[i] & 0xffff0000u);
            s = fmaf(lo, lo, s); s = fmaf(hi, hi, s);
        }
        mx = fmaxf(mx, s);
    }
    #pragma unroll
    for (int o = 16; o > 0; o >>= 1) mx = fmaxf(mx, __shfl_xor_sync(~0u, mx, o));
    __shared__ float sm[8];
    if ((tid & 31) == 0) sm[tid >> 5] = mx;
    __syncthreads();
    if (tid == 0) {
        float m = sm[0];
        for (int i = 1; i < 8; i++) m = fmaxf(m, sm[i]);
        g_kmax2[h] = m;
    }
}

__device__ __noinline__ void attnA_slow_tile(const bf16* __restrict__ Q, const bf16* __restrict__ Kp, const bf16* __restrict__ Vp,
                                             bf16* __restrict__ o, int q0, int h, int lane) {
    const int g = lane >> 2, t = lane & 3;
    uint32_t qa[4];
    qa[0] = *(const uint32_t*)(Q + (q0 + g) * 16 + 2 * t);
    qa[1] = *(const uint32_t*)(Q + (q0 + g + 8) * 16 + 2 * t);
    qa[2] = *(const uint32_t*)(Q + (q0 + g) * 16 + 8 + 2 * t);
    qa[3] = *(const uint32_t*)(Q + (q0 + g + 8) * 16 + 8 + 2 * t);
    const float sc2 = 0.25f * 1.4426950408889634f;
    float m0 = -INFINITY, m1 = -INFINITY, l0 = 0.f, l1 = 0.f;
    float o0[4] = {}, o1[4] = {};
    const unsigned short* Vs = (const unsigned short*)Vp;
    for (int kb = 0; kb < S_LEN; kb += 16) {
        float s[2][4] = {};
        #pragma unroll
        for (int n = 0; n < 2; n++) {
            uint32_t b0 = *(const uint32_t*)(Kp + (kb + n * 8 + g) * 16 + 2 * t);
            uint32_t b1 = *(const uint32_t*)(Kp + (kb + n * 8 + g) * 16 + 8 + 2 * t);
            mma16816(s[n], qa, b0, b1);
        }
        float mx0 = fmaxf(m0, fmaxf(fmaxf(s[0][0], s[0][1]), fmaxf(s[1][0], s[1][1])));
        float mx1 = fmaxf(m1, fmaxf(fmaxf(s[0][2], s[0][3]), fmaxf(s[1][2], s[1][3])));
        mx0 = fmaxf(mx0, __shfl_xor_sync(~0u, mx0, 1)); mx0 = fmaxf(mx0, __shfl_xor_sync(~0u, mx0, 2));
        mx1 = fmaxf(mx1, __shfl_xor_sync(~0u, mx1, 1)); mx1 = fmaxf(mx1, __shfl_xor_sync(~0u, mx1, 2));
        float a0 = ex2((m0 - mx0) * sc2), a1 = ex2((m1 - mx1) * sc2);
        m0 = mx0; m1 = mx1;
        l0 *= a0; l1 *= a1;
        o0[0] *= a0; o0[1] *= a0; o0[2] *= a1; o0[3] *= a1; o1[0] *= a0; o1[1] *= a0; o1[2] *= a1; o1[3] *= a1;
        float p[8];
        p[0] = ex2((s[0][0] - m0) * sc2); p[1] = ex2((s[0][1] - m0) * sc2); p[2] = ex2((s[0][2] - m1) * sc2); p[3] = ex2((s[0][3] - m1) * sc2);
        p[4] = ex2((s[1][0] - m0) * sc2); p[5] = ex2((s[1][1] - m0) * sc2); p[6] = ex2((s[1][2] - m1) * sc2); p[7] = ex2((s[1][3] - m1) * sc2);
        l0 += p[0] + p[1] + p[4] + p[5]; l1 += p[2] + p[3] + p[6] + p[7];
        uint32_t pa[4] = { pack_bf16(p[0], p[1]), pack_bf16(p[2], p[3]), pack_bf16(p[4], p[5]), pack_bf16(p[6], p[7]) };
        #pragma unroll
        for (int n = 0; n < 2; n++) {
            const int d = n * 8 + g;
            uint32_t b0 = (uint32_t)Vs[(kb + 2 * t) * 16 + d] | ((uint32_t)Vs[(kb + 2 * t + 1) * 16 + d] << 16);
            uint32_t b1 = (uint32_t)Vs[(kb + 8 + 2 * t) * 16 + d] | ((uint32_t)Vs[(kb + 8 + 2 * t + 1) * 16 + d] << 16);
            mma16816(n == 0 ? o0 : o1, pa, b0, b1);
        }
    }
    l0 += __shfl_xor_sync(~0u, l0, 1); l0 += __shfl_xor_sync(~0u, l0, 2);
    l1 += __shfl_xor_sync(~0u, l1, 1); l1 += __shfl_xor_sync(~0u, l1, 2);
    float i0 = 1.f / l0, i1 = 1.f / l1;
    *(uint32_t*)(o + (size_t)(q0 + g) * DM + h * 16 + 2 * t) = pack_bf16(o0[0] * i0, o0[1] * i0);
    *(uint32_t*)(o + (size_t)(q0 + g + 8) * DM + h * 16 + 2 * t) = pack_bf16(o0[2] * i1, o0[3] * i1);
    *(uint32_t*)(o + (size_t)(q0 + g) * DM + h * 16 + 8 + 2 * t) = pack_bf16(o1[0] * i0, o1[1] * i0);
    *(uint32_t*)(o + (size_t)(q0 + g + 8) * DM + h * 16 + 8 + 2 * t) = pack_bf16(o1[2] * i1, o1[3] * i1);
}

constexpr int AT_CH = 128;
constexpr int AT_STAGES = 3;
__global__ void __launch_bounds__(128) attnA_kernel(const bf16* __restrict__ qkv, bf16* __restrict__ o) {
    __shared__ __align__(128) uint8_t sm[AT_STAGES * AT_CH * 64];
    const int tid = threadIdx.x, lane = tid & 31, warp = tid >> 5;
    const int h = blockIdx.y, q0 = blockIdx.x * 128 + warp * 32;
    const int g = lane >> 2, t = lane & 3;
    const bf16* Q = qkv + (size_t)(0 * NH + h) * S_LEN * 16;
    const bf16* Kp = qkv + (size_t)(1 * NH + h) * S_LEN * 16;
    const bf16* Vp = qkv + (size_t)(2 * NH + h) * S_LEN * 16;
    const uint32_t sb = smem_u32(sm);
    auto load_stage = [&](int c) {
        const uint32_t base = sb + (c % AT_STAGES) * (AT_CH * 64);
        #pragma unroll
        for (int i = 0; i < 2; i++) {
            int idx = tid + i * 128, r = idx >> 1, cc = idx & 1;
            uint32_t off = r * 32 + ((cc ^ ((r >> 2) & 1)) << 4);
            cp_async16(base + off, Kp + (size_t)(c * AT_CH + r) * 16 + cc * 8);
            cp_async16(base + AT_CH * 32 + off, Vp + (size_t)(c * AT_CH + r) * 16 + cc * 8);
        }
        asm volatile("cp.async.commit_group;" ::: "memory");
    };
    load_stage(0);
    load_stage(1);
    const float sc2 = 0.25f * 1.4426950408889634f;
    uint32_t qa[2][4];
    float nb[2][2];
    {
        const float kmax = sqrtf(g_kmax2[h]) * 1.0001f;
        #pragma unroll
        for (int mt = 0; mt < 2; mt++) {
            const int r0 = q0 + mt * 16 + g;
            qa[mt][0] = *(const uint32_t*)(Q + r0 * 16 + 2 * t);
            qa[mt][1] = *(const uint32_t*)(Q + (r0 + 8) * 16 + 2 * t);
            qa[mt][2] = *(const uint32_t*)(Q + r0 * 16 + 8 + 2 * t);
            qa[mt][3] = *(const uint32_t*)(Q + (r0 + 8) * 16 + 8 + 2 * t);
            #pragma unroll
            for (int hh = 0; hh < 2; hh++) {
                float a0 = __uint_as_float(qa[mt][hh] << 16), a1 = __uint_as_float(qa[mt][hh] & 0xffff0000u);
                float a2 = __uint_as_float(qa[mt][2 + hh] << 16), a3 = __uint_as_float(qa[mt][2 + hh] & 0xffff0000u);
                float n2 = a0 * a0 + a1 * a1 + a2 * a2 + a3 * a3;
                n2 += __shfl_xor_sync(~0u, n2, 1); n2 += __shfl_xor_sync(~0u, n2, 2);
                nb[mt][hh] = -(sqrtf(n2) * 1.0001f * kmax) * sc2;
            }
        }
    }
    float oa[2][3][4] = {};
    const uint32_t ones = 0x3F803F80u;
    const int rk = (lane & 7) + ((lane >> 4) << 3), ck = (lane >> 3) & 1;
    const uint32_t koff = rk * 32 + ((ck ^ ((rk >> 2) & 1)) << 4);
    const int rv = lane & 15, cv = lane >> 4;
    const uint32_t voff = AT_CH * 32 + rv * 32 + ((cv ^ ((rv >> 2) & 1)) << 4);
    constexpr int NCH = S_LEN / AT_CH;
    #pragma unroll 1
    for (int c = 0; c < NCH; c++) {
        asm volatile("cp.async.wait_group 1;" ::: "memory");
        __syncthreads();
        if (c + 2 < NCH) load_stage(c + 2); else asm volatile("cp.async.commit_group;" ::: "memory");
        const uint32_t base = sb + (c % AT_STAGES) * (AT_CH * 64);
        #pragma unroll 2
        for (int j = 0; j < AT_CH / 16; j++) {
            uint32_t kb[4], vb[4];
            ldsm4(kb, base + j * 512 + koff);
            ldsm4t(vb, base + j * 512 + voff);
            #pragma unroll
            for (int mt = 0; mt < 2; mt++) {
                float s0[4] = {}, s1[4] = {};
                mma16816(s0, qa[mt], kb[0], kb[1]);
                mma16816(s1, qa[mt], kb[2], kb[3]);
                uint32_t pa[4];
                pa[0] = pack_bf16(ex2(fmaf(s0[0], sc2, nb[mt][0])), ex2(fmaf(s0[1], sc2, nb[mt][0])));
                pa[1] = pack_bf16(ex2(fmaf(s0[2], sc2, nb[mt][1])), ex2(fmaf(s0[3], sc2, nb[mt][1])));
                pa[2] = pack_bf16(ex2(fmaf(s1[0], sc2, nb[mt][0])), ex2(fmaf(s1[1], sc2, nb[mt][0])));
                pa[3] = pack_bf16(ex2(fmaf(s1[2], sc2, nb[mt][1])), ex2(fmaf(s1[3], sc2, nb[mt][1])));
                mma16816(oa[mt][0], pa, vb[0], vb[1]);
                mma16816(oa[mt][1], pa, vb[2], vb[3]);
                mma16816(oa[mt][2], pa, ones, ones);
            }
        }
    }
    #pragma unroll
    for (int mt = 0; mt < 2; mt++) {
        const float l0 = oa[mt][2][0], l1 = oa[mt][2][2];
        const bool bad = !(l0 > 1e-27f && l1 > 1e-27f && l0 < 1e30f && l1 < 1e30f);
        if (__any_sync(~0u, bad)) {
            attnA_slow_tile(Q, Kp, Vp, o, q0 + mt * 16, h, lane);
        } else {
            const float i0 = 1.f / l0, i1 = 1.f / l1;
            const int r0 = q0 + mt * 16 + g;
            *(uint32_t*)(o + (size_t)r0 * DM + h * 16 + 2 * t) = pack_bf16(oa[mt][0][0] * i0, oa[mt][0][1] * i0);
            *(uint32_t*)(o + (size_t)(r0 + 8) * DM + h * 16 + 2 * t) = pack_bf16(oa[mt][0][2] * i1, oa[mt][0][3] * i1);
            *(uint32_t*)(o + (size_t)r0 * DM + h * 16 + 8 + 2 * t) = pack_bf16(oa[mt][1][0] * i0, oa[mt][1][1] * i0);
            *(uint32_t*)(o + (size_t)(r0 + 8) * DM + h * 16 + 8 + 2 * t) = pack_bf16(oa[mt][1][2] * i1, oa[mt][1][3] * i1);
        }
    }
}

typedef CUresult (*PFN_encodeTiled)(CUtensorMap*, CUtensorMapDataType, cuuint32_t, void*, const cuuint64_t*, const cuuint64_t*,
                                    const cuuint32_t*, const cuuint32_t*, CUtensorMapInterleave, CUtensorMapSwizzle,
                                    CUtensorMapL2promotion, CUtensorMapFloatOOBfill);

static CUtensorMap make_tmap_2d(PFN_encodeTiled enc, const void* ptr, uint64_t inner, uint64_t outer, uint32_t box_inner, uint32_t box_outer) {
    CUtensorMap tm;
    cuuint64_t dims[2] = { inner, outer };
    cuuint64_t strides[1] = { inner * 2 };
    cuuint32_t box[2] = { box_inner, box_outer };
    cuuint32_t es[2] = { 1, 1 };
    enc(&tm, CU_TENSOR_MAP_DATA_TYPE_BFLOAT16, 2, (void*)ptr, dims, strides, box, es, CU_TENSOR_MAP_INTERLEAVE_NONE,
        CU_TENSOR_MAP_SWIZZLE_128B, CU_TENSOR_MAP_L2_PROMOTION_L2_128B, CU_TENSOR_MAP_FLOAT_OOB_FILL_NONE);
    return tm;
}

extern "C" void kernel_launch(void* const* d_in, const int* in_sizes, int n_in, void* d_out, int out_size) {
    const bf16* A_x = (const bf16*)d_in[0];
    const bf16* A_wqkv = (const bf16*)d_in[1];
    const bf16* A_wo = (const bf16*)d_in[2];
    const bf16* B_x = (const bf16*)d_in[3];
    const bf16* B_mem0 = (const bf16*)d_in[4];
    const bf16* B_Wq = (const bf16*)d_in[5];
    const bf16* B_Wk = (const bf16*)d_in[6];
    const bf16* B_Wv = (const bf16*)d_in[7];
    const bf16* B_Wo = (const bf16*)d_in[8];
    bf16* out = (bf16*)d_out;

    static PFN_encodeTiled enc = nullptr;
    static CUtensorMap tmX, tmAx, tmWqkv, tmOA, tmWoA, tmOtok, tmWoB;
    static const void* key[4] = { nullptr, nullptr, nullptr, nullptr };
    static bf16 *p_otok, *p_qkvA, *p_oA;
    static cudaStream_t s2;
    static cudaEvent_t evFork, evJoin;
    if (!enc) {
        cudaStreamCreateWithFlags(&s2, cudaStreamNonBlocking);
        cudaEventCreateWithFlags(&evFork, cudaEventDisableTiming);
        cudaEventCreateWithFlags(&evJoin, cudaEventDisableTiming);
        void* fn = nullptr; cudaDriverEntryPointQueryResult qres;
        cudaGetDriverEntryPoint("cuTensorMapEncodeTiled", &fn, cudaEnableDefault, &qres);
        enc = (PFN_encodeTiled)fn;
        cudaFuncSetAttribute(chain_kernel, cudaFuncAttributeMaxDynamicSharedMemorySize, CH_SMEM_ALLOC);
        cudaFuncSetAttribute(tokattn_kernel, cudaFuncAttributeMaxDynamicSharedMemorySize, 2 * TK_BUF + 16);
        cudaFuncSetAttribute(gemm_tma<0, 1>, cudaFuncAttributeMaxDynamicSharedMemorySize, GM_SMEM);
        cudaFuncSetAttribute(gemm_tma<1, 1>, cudaFuncAttributeMaxDynamicSharedMemorySize, GM_SMEM);
        cudaFuncSetAttribute(gemm_tma<1, 2>, cudaFuncAttributeMaxDynamicSharedMemorySize, GM_SMEM);
        cudaGetSymbolAddress((void**)&p_otok, g_otok);
        cudaGetSymbolAddress((void**)&p_qkvA, g_qkvA);
        cudaGetSymbolAddress((void**)&p_oA, g_oA);
        tmOA = make_tmap_2d(enc, p_oA, 512, 2048, 64, 128);
        tmOtok = make_tmap_2d(enc, p_otok, 4096, 2048, 64, 128);
    }
    if (key[0] != (const void*)B_x || key[1] != (const void*)A_x || key[2] != (const void*)A_wqkv || key[3] != (const void*)B_Wo) {
        tmX = make_tmap_2d(enc, B_x, 512, 2048, 64, 32);
        tmAx = make_tmap_2d(enc, A_x, 512, 2048, 64, 128);
        tmWqkv = make_tmap_2d(enc, A_wqkv, 1536, 512, 64, 64);
        tmWoA = make_tmap_2d(enc, A_wo, 512, 512, 64, 64);
        tmWoB = make_tmap_2d(enc, B_Wo, 512, 4096, 64, 64);
        key[0] = B_x; key[1] = A_x; key[2] = A_wqkv; key[3] = B_Wo;
    }

    cudaStream_t st = cudaStreamPerThread;
    cudaEventRecord(evFork, st);
    cudaStreamWaitEvent(s2, evFork, 0);
    chain_kernel<<<96, 384, CH_SMEM_ALLOC, st>>>(tmX, B_mem0, B_Wq, B_Wk, B_Wv, B_Wo);
    gemm_tma<0, 1><<<16 * 12, 288, GM_SMEM, s2>>>(tmAx, tmWqkv, p_qkvA, 512, 12, 0, 0);
    knorm_kernel<<<NH, 256, 0, s2>>>(p_qkvA);
    attnA_kernel<<<dim3(2048 / 128, NH), 128, 0, s2>>>(p_qkvA, p_oA);
    gemm_tma<1, 1><<<16 * 4, 288, GM_SMEM, s2>>>(tmOA, tmWoA, out, 512, 4, 1024, 0);
    cudaEventRecord(evJoin, s2);
    tokattn_kernel<<<132 * 3, 128, 2 * TK_BUF + 16, st>>>(0, NSEG * NH);
    {
        cudaLaunchConfig_t cfg = {};
        cfg.gridDim = dim3(16 * 4 * 2); cfg.blockDim = dim3(288); cfg.dynamicSmemBytes = GM_SMEM; cfg.stream = st;
        cudaLaunchAttribute at[1]; at[0].id = cudaLaunchAttributeClusterDimension; at[0].val.clusterDim.x = 2; at[0].val.clusterDim.y = 1; at[0].val.clusterDim.z = 1;
        cfg.attrs = at; cfg.numAttrs = 1;
        cudaLaunchKernelEx(&cfg, gemm_tma<1, 2>, tmOtok, tmWoB, out, 4096, 4, 1024, 512);
    }
    cudaStreamWaitEvent(st, evJoin, 0);
}
```

```cpp
#include <cuda_runtime.h>
#include <cuda_bf16.h>
#include <cuda.h>
#include <stdint.h>

typedef __nv_bfloat16 bf16;

constexpr int S_LEN = 2048;
constexpr int DM = 512;
constexpr int NH = 32;
constexpr int A_DH = 16;
constexpr int B_DH = 128;
constexpr int B_M = 8;
constexpr int SEG = 32;
constexpr int NSEG = 64;

__device__ float4 g_acc[NSEG][12][4][32];
__device__ unsigned g_gridbar;
__device__ bf16 g_otok[S_LEN * NH * B_DH];
__device__ bf16 g_qkvA[3 * NH * S_LEN * A_DH];
__device__ bf16 g_oA[S_LEN * DM];

#define TSTAMP(i) do {} while (0)
__device__ __forceinline__ uint32_t smem_u32(const void* p) { return (uint32_t)__cvta_generic_to_shared(p); }
__device__ __forceinline__ uint32_t mapa(uint32_t a, uint32_t r) {
    uint32_t o; asm volatile("mapa.shared::cluster.u32 %0, %1, %2;" : "=r"(o) : "r"(a), "r"(r)); return o;
}
__device__ __forceinline__ void mbar_init(uint32_t a, uint32_t c) { asm volatile("mbarrier.init.shared.b64 [%0], %1;" :: "r"(a), "r"(c)); }
__device__ __forceinline__ void mbar_expect(uint32_t a, uint32_t b) {
    asm volatile("mbarrier.arrive.expect_tx.shared.b64 _, [%0], %1;" :: "r"(a), "r"(b) : "memory");
}
__device__ __forceinline__ void mbar_arrive(uint32_t a) {
    asm volatile("mbarrier.arrive.shared.b64 _, [%0];" :: "r"(a) : "memory");
}
__device__ __forceinline__ bool mbar_try(uint32_t a, uint32_t par) {
    uint32_t ok;
    asm volatile("{\n.reg .pred p;\nmbarrier.try_wait.parity.shared::cta.b64 p, [%1], %2;\nselp.u32 %0, 1, 0, p;\n}"
                 : "=r"(ok) : "r"(a), "r"(par) : "memory");
    return ok != 0;
}
__device__ __forceinline__ void mbar_wait(uint32_t a, uint32_t par) {
    #pragma unroll 1
    for (int it = 0; it < 4000000; it++) { if (mbar_try(a, par)) return; }
}
__device__ __forceinline__ void st_async_b32(uint32_t a, uint32_t x, uint32_t mb) {
    asm volatile("st.async.shared::cluster.mbarrier::complete_tx::bytes.b32 [%0], %1, [%2];" :: "r"(a), "r"(x), "r"(mb) : "memory");
}
__device__ __forceinline__ void st_async_v4(uint32_t a, uint32_t x, uint32_t y, uint32_t z, uint32_t w, uint32_t mb) {
    asm volatile("st.async.shared::cluster.mbarrier::complete_tx::bytes.v4.b32 [%0], {%1,%2,%3,%4}, [%5];"
                 :: "r"(a), "r"(x), "r"(y), "r"(z), "r"(w), "r"(mb) : "memory");
}
__device__ __forceinline__ void bulk_s2s(uint32_t dst, uint32_t src, uint32_t bytes, uint32_t mb) {
    asm volatile("cp.async.bulk.shared::cluster.shared::cta.mbarrier::complete_tx::bytes [%0], [%1], %2, [%3];"
                 :: "r"(dst), "r"(src), "r"(bytes), "r"(mb) : "memory");
}
__device__ __forceinline__ void cluster_sync() {
    asm volatile("barrier.cluster.arrive.aligned;\nbarrier.cluster.wait.aligned;" ::: "memory");
}
__device__ __forceinline__ float4 ld_relaxed_f4(const float4* p) {
    float4 v;
    asm volatile("ld.relaxed.gpu.global.v4.f32 {%0,%1,%2,%3}, [%4];" : "=f"(v.x), "=f"(v.y), "=f"(v.z), "=f"(v.w) : "l"(p) : "memory");
    return v;
}
__device__ __forceinline__ void red_v4(float4* p, float a, float b, float c, float d) {
    asm volatile("red.relaxed.gpu.global.add.v4.f32 [%0], {%1,%2,%3,%4};" :: "l"(p), "f"(a), "f"(b), "f"(c), "f"(d) : "memory");
}
__device__ __forceinline__ void ldsm4(uint32_t* r, uint32_t a) {
    asm volatile("ldmatrix.sync.aligned.m8n8.x4.shared.b16 {%0,%1,%2,%3}, [%4];"
                 : "=r"(r[0]), "=r"(r[1]), "=r"(r[2]), "=r"(r[3]) : "r"(a) : "memory");
}
__device__ __forceinline__ void ldsm4t(uint32_t* r, uint32_t a) {
    asm volatile("ldmatrix.sync.aligned.m8n8.x4.trans.shared.b16 {%0,%1,%2,%3}, [%4];"
                 : "=r"(r[0]), "=r"(r[1]), "=r"(r[2]), "=r"(r[3]) : "r"(a) : "memory");
}
__device__ __forceinline__ void ldsm2(uint32_t* r, uint32_t a) {
    asm volatile("ldmatrix.sync.aligned.m8n8.x2.shared.b16 {%0,%1}, [%2];"
                 : "=r"(r[0]), "=r"(r[1]) : "r"(a) : "memory");
}
__device__ __forceinline__ void mma16816(float* c, const uint32_t* a, uint32_t b0, uint32_t b1) {
    asm volatile("mma.sync.aligned.m16n8k16.row.col.f32.bf16.bf16.f32 {%0,%1,%2,%3}, {%4,%5,%6,%7}, {%8,%9}, {%0,%1,%2,%3};"
                 : "+f"(c[0]), "+f"(c[1]), "+f"(c[2]), "+f"(c[3])
                 : "r"(a[0]), "r"(a[1]), "r"(a[2]), "r"(a[3]), "r"(b0), "r"(b1));
}
__device__ __forceinline__ uint32_t pack_bf16(float lo, float hi) {
    uint32_t r; asm("cvt.rn.bf16x2.f32 %0, %1, %2;" : "=r"(r) : "f"(hi), "f"(lo)); return r;
}
__device__ __forceinline__ uint32_t pack_bf16_trunc(float lo, float hi) { return __byte_perm(__float_as_uint(lo), __float_as_uint(hi), 0x7632); }
__device__ __forceinline__ float ex2(float x) { float y; asm("ex2.approx.ftz.f32 %0, %1;" : "=f"(y) : "f"(x)); return y; }
__device__ __forceinline__ float ex2_fma(float x) {
    x = fmaxf(x, -126.f);
    const float tt = x + 12582912.f;
    const float r = x - (tt - 12582912.f);
    float p = fmaf(0.0013276461977511644f, r, 0.009675540961325169f);
    p = fmaf(p, r, 0.05550713464617729f);
    p = fmaf(p, r, 0.24022120237350464f);
    p = fmaf(p, r, 0.6931469440460205f);
    p = fmaf(p, r, 1.0000001192092896f);
    return __int_as_float(__float_as_int(p) + (__float_as_int(tt) << 23));
}
__device__ __forceinline__ void cp_async16(uint32_t dst, const void* src) {
    asm volatile("cp.async.cg.shared.global [%0], [%1], 16;" :: "r"(dst), "l"(src) : "memory");
}
__device__ __forceinline__ void cp_async_wait_all() { asm volatile("cp.async.wait_all;" ::: "memory"); }
__device__ __forceinline__ void named_bar(int id, int n) { asm volatile("bar.sync %0, %1;" :: "r"(id), "r"(n) : "memory"); }
__device__ __forceinline__ uint64_t make_desc(uint32_t saddr, uint32_t lbo, uint32_t sbo, uint32_t swz) {
    uint64_t d = 0;
    d |= (uint64_t)((saddr & 0x3FFFF) >> 4);
    d |= (uint64_t)((lbo >> 4) & 0x3FFF) << 16;
    d |= (uint64_t)((sbo >> 4) & 0x3FFF) << 32;
    d |= (uint64_t)swz << 62;
    return d;
}
__device__ __forceinline__ void wg_fence() { asm volatile("wgmma.fence.sync.aligned;" ::: "memory"); }
__device__ __forceinline__ void wg_commit() { asm volatile("wgmma.commit_group.sync.aligned;" ::: "memory"); }
template <int N> __device__ __forceinline__ void wg_wait() { asm volatile("wgmma.wait_group.sync.aligned %0;" :: "n"(N) : "memory"); }
__device__ __forceinline__ void wgmma_rs_n32(float* d, const uint32_t* a, uint64_t desc, int scale_d) {
    asm volatile("{\n.reg .pred p;\nsetp.ne.b32 p, %21, 0;\n"
                 "wgmma.mma_async.sync.aligned.m64n32k16.f32.bf16.bf16 {%0,%1,%2,%3,%4,%5,%6,%7,%8,%9,%10,%11,%12,%13,%14,%15}, {%16,%17,%18,%19}, %20, p, 1, 1, 0;\n}"
                 : "+f"(d[0]), "+f"(d[1]), "+f"(d[2]), "+f"(d[3]), "+f"(d[4]), "+f"(d[5]), "+f"(d[6]), "+f"(d[7]),
                   "+f"(d[8]), "+f"(d[9]), "+f"(d[10]), "+f"(d[11]), "+f"(d[12]), "+f"(d[13]), "+f"(d[14]), "+f"(d[15])
                 : "r"(a[0]), "r"(a[1]), "r"(a[2]), "r"(a[3]), "l"(desc), "r"(scale_d));
}
__device__ __forceinline__ void tma_load_2d_mc(uint32_t dst, const CUtensorMap* tm, int c0, int c1, uint32_t mb, uint16_t mask) {
    asm volatile("cp.async.bulk.tensor.2d.shared::cluster.global.mbarrier::complete_tx::bytes.multicast::cluster [%0], [%1, {%3, %4}], [%2], %5;"
                 :: "r"(dst), "l"(tm), "r"(mb), "r"(c0), "r"(c1), "h"(mask) : "memory");
}
__device__ __forceinline__ void tma_load_2d(uint32_t dst, const CUtensorMap* tm, int c0, int c1, uint32_t mb) {
    asm volatile("cp.async.bulk.tensor.2d.shared::cluster.global.mbarrier::complete_tx::bytes [%0], [%1, {%3, %4}], [%2];"
                 :: "r"(dst), "l"(tm), "r"(mb), "r"(c0), "r"(c1) : "memory");
}

constexpr int CH_XS = 0;
constexpr int CH_KX = 65536;
constexpr int CH_VX = CH_KX + 30720;
constexpr int CH_QX = CH_VX + 30720;
constexpr int CH_SB2 = CH_QX + 36864;
constexpr int CH_MEMT = CH_SB2 + 2560;
constexpr int CH_KM = CH_MEMT + 8192;
constexpr int CH_VM = CH_KM + 4096;
constexpr int CH_QM = CH_VM + 4096;
constexpr int CH_SB = CH_QM + 2048;
constexpr int CH_OB = CH_SB + 1280;
constexpr int CH_BAR = CH_OB + 2048;
constexpr int CH_SMEM = CH_BAR + 128;
constexpr int CH_SMEM_ALLOC = 192 * 1024;
#define POLL_DELAY 900
constexpr int TOKP = 80;
constexpr int WOP = 400;

template <int J0, int J1>
__device__ __forceinline__ void qkv_range(float (&c)[4][4], const uint32_t (&wr)[32][4], uint32_t memt_lane) {
    #pragma unroll
    for (int j = J0; j < J1; j++) {
        uint32_t b[4];
        ldsm4t(b, memt_lane + j * 512);
        mma16816(c[(2 * j) & 3], wr[2 * j], b[0], b[1]);
        mma16816(c[(2 * j + 1) & 3], wr[2 * j + 1], b[2], b[3]);
    }
}
__device__ __forceinline__ void bar_arrive(int id, int n) { asm volatile("bar.arrive %0, %1;" :: "r"(id), "r"(n) : "memory"); }

__global__ void __cluster_dims__(3, 1, 1) __launch_bounds__(384, 1)
chain_kernel(const __grid_constant__ CUtensorMap tmX, const bf16* __restrict__ mem0,
             const bf16* __restrict__ Wq, const bf16* __restrict__ Wk, const bf16* __restrict__ Wv,
             const bf16* __restrict__ Wo) {
    extern __shared__ __align__(1024) uint8_t smem[];
    const uint32_t sb = smem_u32(smem);
    uint32_t rank; asm volatile("mov.u32 %0, %%cluster_ctarank;" : "=r"(rank));
    const int tid = threadIdx.x, lane = tid & 31, warp = tid >> 5, wg = warp >> 2, w4 = warp & 3;
    const int g = lane >> 2, t = lane & 3;
    const int head = blockIdx.x / 3;
    const uint32_t barMem = sb + CH_BAR, barQK = barMem + 8, barV = barMem + 16, barTok = barMem + 24  , barX = barMem + 48  ;

    if (tid == 0) {
        mbar_init(barMem, 1); mbar_init(barQK, rank == 2 ? 1 : 9); mbar_init(barV, rank == 2 ? 9 : 1);
        mbar_init(barTok, 1); mbar_init(barTok + 8, 1); mbar_init(barTok + 16, 1); mbar_init(barX, 1); mbar_init(barX + 8, 1);
        asm volatile("fence.mbarrier_init.release.cluster;" ::: "memory");
    }
    {
        float4* p = &g_acc[0][0][0][0];
        constexpr int TOT = NSEG * 12 * 4 * 32;
        for (int i = blockIdx.x * 384 + tid; i < TOT; i += 96 * 384) p[i] = make_float4(0.f, 0.f, 0.f, 0.f);
    }
    const int tile0 = rank * 12 + w4 * 3;
    {
        const bf16* W = (rank == 0) ? Wq : (rank == 1 ? Wk : Wv);
        const int nf = (rank == 2) ? 128 : 192;
        for (int i = tid; i < 512 * 16; i += 384) {
            int d = i >> 4, c = i & 15;
            cp_async16(sb + (c >> 3) * 65536 + d * 128 + (((c & 7) ^ (d & 7)) << 4), W + (size_t)d * 4096 + head * 128 + c * 8);
        }
        for (int i = tid; i < 128 * (nf / 8); i += 384) {
            int e = i / (nf / 8), c = i % (nf / 8);
            cp_async16(sb + 131072 + e * WOP + c * 16, Wo + (size_t)(head * 128 + e) * 512 + rank * 192 + c * 8);
        }
        cp_async_wait_all();
        __threadfence();
        __syncthreads();
    }
    const uint32_t pr0 = mapa(sb, rank == 0 ? 1 : 0), pr1 = mapa(sb, rank == 2 ? 1 : 2);
    const uint32_t self = mapa(sb, rank);
    const int mi = lane >> 3, r8 = lane & 7;

    if (wg == 2) {
        asm volatile("setmaxnreg.dec.sync.aligned.u32 152;");
        uint32_t wr[24][4];
        #pragma unroll
        for (int i = 0; i < 3; i++)
            #pragma unroll
            for (int kk = 0; kk < 8; kk++) {
                if (tile0 + i < 32) ldsm4t(wr[i * 8 + kk], sb + 131072 + (kk * 16 + (mi >> 1) * 8 + r8) * WOP + ((w4 * 3 + i) * 16 + (mi & 1) * 8) * 2);
                else { wr[i * 8 + kk][0] = 0; wr[i * 8 + kk][1] = 0; wr[i * 8 + kk][2] = 0; wr[i * 8 + kk][3] = 0; }
            }
        unsigned bar_target = 0;
        if (tid == 256) {
            unsigned ticket = atomicAdd(&g_gridbar, 1u);
            bar_target = (ticket / 96u + 1u) * 96u;
        }
        cluster_sync();
        const bool boss = (tid == 256 + 96);
        const uint32_t mem_remote_bytes = 8192 - ((rank == 2) ? 2048 : 3072);
        const uint32_t tok_bytes = (rank == 0) ? 20480 : 16384;
        const int nvalid = min(max(32 - tile0, 0), 3);
        const int slot = rank * 4 + w4;
        auto issue_x = [&](int seg) {
            mbar_expect(barX + (seg & 1) * 8, 32768);
            #pragma unroll 1
            for (int c = rank; c < 8; c += 3)
                tma_load_2d_mc(sb + CH_XS + (seg & 1) * 32768 + c * 4096, &tmX, c * 64, seg * SEG, barX + (seg & 1) * 8, (uint16_t)7);
        };
        if (boss) {
            mbar_expect(barTok, tok_bytes); mbar_expect(barTok + 8, tok_bytes); mbar_expect(barTok + 16, tok_bytes);
            issue_x(0); issue_x(1);
        }
        auto tok_attn = [&](int seg) {
            const float sc2 = 0.08838834764831845f * 1.4426950408889634f;
            const int mt = rank - 1;
            const uint32_t sQ = sb + CH_QX + (seg % 3) * 12288, sK = sb + CH_KX + (seg % 3) * 10240, sV = sb + CH_VX + (seg % 3) * 10240;
            const uint32_t sKM = sb + CH_KM + (seg & 1) * 2048, sVM = sb + CH_VM + (seg & 1) * 2048;
            {
                float c0[2][4] = {}, c1[2][4] = {};
                #pragma unroll
                for (int j = 0; j < 4; j++) {
                    uint32_t qa[2][4], bb[4];
                    #pragma unroll
                    for (int h2 = 0; h2 < 2; h2++) {
                        const int dim = j * 32 + h2 * 16 + (mi >> 1) * 8 + r8;
                        ldsm4t(qa[h2], sQ + dim * 48 + (mi & 1) * 16);
                    }
                    ldsm4t(bb, sK + (j * 32 + lane) * TOKP + w4 * 16);
                    mma16816(c1[0], qa[0], bb[0], bb[1]);
                    mma16816(c1[1], qa[1], bb[2], bb[3]);
                    if (w4 == 3) {
                        ldsm4t(bb, sKM + (j * 32 + lane) * 16);
                        mma16816(c0[0], qa[0], bb[0], bb[1]);
                        mma16816(c0[1], qa[1], bb[2], bb[3]);
                    }
                }
                *(float4*)(smem + CH_SB2 + (w4 + 1) * 512 + lane * 16) = make_float4(c1[0][0] + c1[1][0], c1[0][1] + c1[1][1], c1[0][2] + c1[1][2], c1[0][3] + c1[1][3]);
                if (w4 == 3) *(float4*)(smem + CH_SB2 + lane * 16) = make_float4(c0[0][0] + c0[1][0], c0[0][1] + c0[1][1], c0[0][2] + c0[1][2], c0[0][3] + c0[1][3]);
            }
            named_bar(7, 128);
            float sc[5][4];
            #pragma unroll
            for (int i = 0; i < 5; i++) {
                float4 x = *(const float4*)(smem + CH_SB2 + i * 512 + lane * 16);
                sc[i][0] = x.x; sc[i][1] = x.y; sc[i][2] = x.z; sc[i][3] = x.w;
            }
            const int tq0 = 8 * (g >> 1) + 2 * (2 * mt) + (g & 1);
            const int tq1 = tq0 + 2;
            float m0 = fmaxf(sc[0][0], sc[0][1]), m1 = fmaxf(sc[0][2], sc[0][3]);
            #pragma unroll
            for (int i = 1; i < 5; i++) {
                #pragma unroll
                for (int e2 = 0; e2 < 2; e2++) {
                    int tk = 8 * t + 2 * (i - 1) + e2;
                    if (tk > tq0) sc[i][e2] = -INFINITY;
                    if (tk > tq1) sc[i][2 + e2] = -INFINITY;
                    m0 = fmaxf(m0, sc[i][e2]); m1 = fmaxf(m1, sc[i][2 + e2]);
                }
            }
            m0 = fmaxf(m0, __shfl_xor_sync(~0u, m0, 1)); m0 = fmaxf(m0, __shfl_xor_sync(~0u, m0, 2));
            m1 = fmaxf(m1, __shfl_xor_sync(~0u, m1, 1)); m1 = fmaxf(m1, __shfl_xor_sync(~0u, m1, 2));
            float l0 = 0.f, l1 = 0.f;
            const float ms0 = -m0 * sc2, ms1 = -m1 * sc2;
            uint32_t pp[3][4];
            #pragma unroll
            for (int i = 0; i < 5; i++) {
                sc[i][0] = ex2(fmaf(sc[i][0], sc2, ms0)); sc[i][1] = ex2(fmaf(sc[i][1], sc2, ms0));
                sc[i][2] = ex2(fmaf(sc[i][2], sc2, ms1)); sc[i][3] = ex2(fmaf(sc[i][3], sc2, ms1));
                l0 += sc[i][0] + sc[i][1]; l1 += sc[i][2] + sc[i][3];
                pp[i >> 1][(i & 1) * 2] = pack_bf16(sc[i][0], sc[i][1]); pp[i >> 1][(i & 1) * 2 + 1] = pack_bf16(sc[i][2], sc[i][3]);
            }
            pp[2][2] = 0; pp[2][3] = 0;
            l0 += __shfl_xor_sync(~0u, l0, 1); l0 += __shfl_xor_sync(~0u, l0, 2);
            l1 += __shfl_xor_sync(~0u, l1, 1); l1 += __shfl_xor_sync(~0u, l1, 2);
            const float i0 = __fdividef(1.f, l0), i1 = __fdividef(1.f, l1);
            bf16* o0p = g_otok + (size_t)(seg * SEG + tq0) * 4096 + head * 128 + w4 * 32 + 2 * t;
            bf16* o1p = o0p + 2 * 4096;
            #pragma unroll
            for (int nt = 0; nt < 4; nt++) {
                uint32_t vx[4], vm[2];
                const int dim = w4 * 32 + nt * 8 + r8;
                ldsm4(vx, sV + dim * TOKP + mi * 16);
                ldsm2(vm, sVM + dim * 16);
                float c[4] = {}, d[4] = {};
                mma16816(c, pp[0], vm[0], vx[0]);
                mma16816(d, pp[1], vx[1], vx[2]);
                mma16816(c, pp[2], vx[3], 0u);
                *(uint32_t*)(o0p + nt * 8) = pack_bf16((c[0] + d[0]) * i0, (c[1] + d[1]) * i0);
                *(uint32_t*)(o1p + nt * 8) = pack_bf16((c[2] + d[2]) * i1, (c[3] + d[3]) * i1);
            }
        };
        long long t_red = clock64();
        #pragma unroll 1
        for (int s = 0; s < NSEG; s++) {
            const int par = s & 1;
            const int tb = s % 3, tph = (s / 3) & 1;
            TSTAMP(0);
            if (boss) { mbar_expect(barMem, mem_remote_bytes); mbar_expect(barQK, rank == 2 ? 4096 : 2048); mbar_expect(barV, rank == 2 ? 0 : 2048); }
            if (nvalid > 0) {
                float v[12];
                if (s == 0) {
                    #pragma unroll
                    for (int i = 0; i < 3; i++)
                        #pragma unroll
                        for (int hf = 0; hf < 2; hf++) {
                            int f = min((tile0 + i) * 16 + hf * 8 + g, 511);
                            v[i * 4 + hf * 2] = __bfloat162float(mem0[(2 * t) * 512 + f]);
                            v[i * 4 + hf * 2 + 1] = __bfloat162float(mem0[(2 * t + 1) * 512 + f]);
                        }
                } else {
                    const float4* src = &g_acc[s][slot][0][lane];
                    while (clock64() - t_red < POLL_DELAY) {}
                    float4 a, b, c, d;
                    d = make_float4(0.f, 0.f, 0.f, 32.f);
                    #pragma unroll 1
                    for (int it = 0; it < 2000000; it++) {
                        a = ld_relaxed_f4(src); b = ld_relaxed_f4(src + 32); c = ld_relaxed_f4(src + 64);
                        if (nvalid == 3) d = ld_relaxed_f4(src + 96);
                        if (a.w == 32.f && b.w == 32.f && c.w == 32.f && d.w == 32.f) break;
                    }
                    v[0] = a.x; v[1] = a.y; v[2] = a.z; v[3] = b.x; v[4] = b.y; v[5] = b.z;
                    v[6] = c.x; v[7] = c.y; v[8] = c.z; v[9] = d.x; v[10] = d.y; v[11] = d.z;
                }
                TSTAMP(1);
                const uint32_t off0 = CH_MEMT + (tile0 * 16 + g) * 16 + t * 4;
                uint32_t wv[6];
                #pragma unroll
                for (int q = 0; q < 6; q++) wv[q] = pack_bf16(v[2 * q], v[2 * q + 1]);
                #pragma unroll
                for (int q = 0; q < 6; q++) if (q < 4 || nvalid == 3) st_async_b32(pr0 + off0 + q * 128, wv[q], pr0 + CH_BAR);
                #pragma unroll
                for (int q = 0; q < 6; q++) if (q < 4 || nvalid == 3) st_async_b32(pr1 + off0 + q * 128, wv[q], pr1 + CH_BAR);
                #pragma unroll
                for (int q = 0; q < 6; q++) if (q < 4 || nvalid == 3) asm volatile("st.shared.b32 [%0], %1;" :: "r"(sb + off0 + q * 128), "r"(wv[q]) : "memory");
            }
            bar_arrive(1, 384);
            if (rank != 0 && s > 0) tok_attn(s - 1);
            TSTAMP(3);
            if (boss) {
                mbar_wait(barQK, par); mbar_wait(barV, par);
                if (s == 0) issue_x(2);
                if (s + 3 < NSEG) { issue_x(s + 3); }
                mbar_wait(barTok + tb * 8, tph);
                if (s + 3 < NSEG) mbar_expect(barTok + tb * 8, tok_bytes);
            }
            __syncwarp();
            if (s + 1 < NSEG) {
                named_bar(3, 384);
                TSTAMP(6);
                if (nvalid > 0) {
                    float c[6][4] = {};
                    #pragma unroll
                    for (int kk = 0; kk < 8; kk++) {
                        uint2 ob = *(const uint2*)(smem + CH_OB + kk * 256 + lane * 8);
                        #pragma unroll
                        for (int i = 0; i < 3; i++) mma16816(c[i * 2 + (kk & 1)], wr[i * 8 + kk], ob.x, ob.y);
                    }
                    if (s == 0) {
                        if (tid == 256) {
                            for (int it = 0; it < 2000000; it++) {
                                unsigned v; asm volatile("ld.acquire.gpu.global.u32 %0, [%1];" : "=r"(v) : "l"(&g_gridbar) : "memory");
                                if ((int)(v - bar_target) >= 0) break;
                            }
                        }
                    }
                    TSTAMP(13);
                    float o[12];
                    #pragma unroll
                    for (int i = 0; i < 3; i++)
                        #pragma unroll
                        for (int e = 0; e < 4; e++) o[i * 4 + e] = c[2 * i][e] + c[2 * i + 1][e];
                    bar_arrive(6, 384);
                    if (s == 0) named_bar(5, (rank == 2) ? 96 : 128);
                    float4* dst = &g_acc[s + 1][slot][0][lane];
                    red_v4(dst, o[0], o[1], o[2], 1.f);
                    red_v4(dst + 32, o[3], o[4], o[5], 1.f);
                    red_v4(dst + 64, o[6], o[7], o[8], 1.f);
                    if (nvalid == 3) red_v4(dst + 96, o[9], o[10], o[11], 1.f);
                } else {
                    bar_arrive(6, 384);
                }
                t_red = clock64();
                TSTAMP(7);
            }
        }
        if (rank != 0) {
            mbar_wait(barQK, (NSEG - 1) & 1); mbar_wait(barV, (NSEG - 1) & 1);
            mbar_wait(barTok + ((NSEG - 1) % 3) * 8, ((NSEG - 1) / 3) & 1);
            named_bar(7, 128);
            tok_attn(NSEG - 1);
        }
    } else {
        asm volatile("setmaxnreg.inc.sync.aligned.u32 176;");
        uint32_t wr[32][4];
        #pragma unroll
        for (int kk = 0; kk < 32; kk++) {
            int d = kk * 16 + (mi >> 1) * 8 + r8;
            int c = w4 * 2 + (mi & 1);
            ldsm4t(wr[kk], sb + wg * 65536 + d * 128 + ((c ^ (d & 7)) << 4));
        }
        cluster_sync();
        float xacc[16];
        auto xproj = [&](int seg) {
            mbar_wait(barX + (seg & 1) * 8, (seg >> 1) & 1);
            wg_fence();
            #pragma unroll
            for (int kk = 0; kk < 32; kk++) {
                uint64_t desc = make_desc(sb + CH_XS + (seg & 1) * 32768 + (kk >> 2) * 4096 + (kk & 3) * 32, 16, 1024, 1);
                wgmma_rs_n32(xacc, wr[kk], desc, kk > 0);
            }
            wg_commit();
            wg_wait<0>();
            const int buf = seg % 3;
            uint32_t p0[4], p1[4];
            #pragma unroll
            for (int j = 0; j < 4; j++) { p0[j] = pack_bf16(xacc[4 * j], xacc[4 * j + 1]); p1[j] = pack_bf16(xacc[4 * j + 2], xacc[4 * j + 3]); }
            const int e = wg * 64 + w4 * 16 + g;
            {
                const uint32_t a = (rank == 0) ? sb + CH_QX + buf * 12288 + (t >> 1) * 6144 + e * 48 + (t & 1) * 16
                                               : sb + ((rank == 1) ? CH_KX : CH_VX) + buf * 10240 + e * TOKP + t * 16;
                const uint32_t a8 = a + 8 * ((rank == 0) ? 48 : TOKP);
                asm volatile("st.shared.v4.b32 [%0], {%1,%2,%3,%4};" :: "r"(a), "r"(p0[0]), "r"(p0[1]), "r"(p0[2]), "r"(p0[3]) : "memory");
                asm volatile("st.shared.v4.b32 [%0], {%1,%2,%3,%4};" :: "r"(a8), "r"(p1[0]), "r"(p1[1]), "r"(p1[2]), "r"(p1[3]) : "memory");
                asm volatile("fence.proxy.async.shared::cta;" ::: "memory");
            }
        };
        auto tok_bcast = [&](int seg) {
            if (tid == 224) {
                const int buf = seg % 3;
                if (rank != 0) {
                    const uint32_t boff = ((rank == 1) ? CH_KX : CH_VX) + buf * 10240;
                    bulk_s2s(pr0 + boff, sb + boff, 10240, pr0 + CH_BAR + 24 + buf * 8);
                    bulk_s2s(pr1 + boff, sb + boff, 10240, pr1 + CH_BAR + 24 + buf * 8);
                } else {
                    const uint32_t boff = CH_QX + buf * 12288;
                    bulk_s2s(pr0 + boff, sb + boff, 6144, pr0 + CH_BAR + 24 + buf * 8);
                    bulk_s2s(pr1 + boff, sb + boff + 6144, 6144, pr1 + CH_BAR + 24 + buf * 8);
                }
            }
        };
        xproj(0);
        xproj(1);
        named_bar(4, 256);
        tok_bcast(0);
        const float sc2 = 0.08838834764831845f * 1.4426950408889634f;
        const uint32_t memt_lane = sb + CH_MEMT + lane * 16;

        #pragma unroll 1
        for (int s = 0; s < NSEG; s++) {
            const int par = s & 1;
            const int tb = s % 3, tph = (s / 3) & 1;
            TSTAMP(0);
            named_bar(1, 384);
            TSTAMP(1);
            {
                float c[4][4] = {};
                if (rank == 0) {
                    qkv_range<0, 6>(c, wr, memt_lane);
                    mbar_wait(barMem, par); TSTAMP(2);
                    qkv_range<6, 16>(c, wr, memt_lane);
                } else if (rank == 1) {
                    qkv_range<6, 12>(c, wr, memt_lane);
                    mbar_wait(barMem, par); TSTAMP(2);
                    qkv_range<0, 6>(c, wr, memt_lane);
                    qkv_range<12, 16>(c, wr, memt_lane);
                } else {
                    qkv_range<12, 16>(c, wr, memt_lane);
                    mbar_wait(barMem, par); TSTAMP(2);
                    qkv_range<0, 12>(c, wr, memt_lane);
                }
                float r0 = (c[0][0] + c[1][0]) + (c[2][0] + c[3][0]);
                float r1 = (c[0][1] + c[1][1]) + (c[2][1] + c[3][1]);
                float r2 = (c[0][2] + c[1][2]) + (c[2][2] + c[3][2]);
                float r3 = (c[0][3] + c[1][3]) + (c[2][3] + c[3][3]);
                uint32_t w0 = pack_bf16(r0, r1), w1 = pack_bf16(r2, r3);
                TSTAMP(10);
                const int e = wg * 64 + w4 * 16 + g;
                uint32_t off = (rank == 0 ? CH_QM : (rank == 1 ? CH_KM + par * 2048 : CH_VM + par * 2048)) + e * 16 + t * 4;
                uint32_t boff = CH_BAR + (rank == 2 ? 16 : 8);
                st_async_b32(pr0 + off, w0, pr0 + boff);
                st_async_b32(pr0 + off + 128, w1, pr0 + boff);
                st_async_b32(pr1 + off, w0, pr1 + boff);
                st_async_b32(pr1 + off + 128, w1, pr1 + boff);
                asm volatile("st.shared.b32 [%0], %1;" :: "r"(sb + off), "r"(w0) : "memory");
                asm volatile("st.shared.b32 [%0], %1;" :: "r"(sb + off + 128), "r"(w1) : "memory");
                __syncwarp();
                if (lane == 0) mbar_arrive(sb + boff);
            }
            TSTAMP(3);
            mbar_wait(barTok + tb * 8, tph);
            uint32_t kb[4][4];
            if (warp >= 1 && warp < 5) {
                #pragma unroll
                for (int j = 0; j < 4; j++)
                    ldsm4t(kb[j], sb + CH_KX + tb * 10240 + (j * 32 + lane) * TOKP + (warp - 1) * 16);
            }
            mbar_wait(barQK, par);
            TSTAMP(4);
            if (warp < 5) {
                if (warp == 0) {
                    #pragma unroll
                    for (int j = 0; j < 4; j++) ldsm4t(kb[j], sb + CH_KM + par * 2048 + (j * 32 + lane) * 16);
                }
                float c[4][4] = {};
                uint32_t q[4][4];
                #pragma unroll
                for (int j = 0; j < 4; j++) ldsm4t(q[j], sb + CH_QM + (j * 32 + lane) * 16);
                #pragma unroll
                for (int j = 0; j < 4; j++) {
                    uint32_t a0[4] = { q[j][0], q[j][0], q[j][1], q[j][1] };
                    uint32_t a1[4] = { q[j][2], q[j][2], q[j][3], q[j][3] };
                    mma16816(c[(2 * j) & 3], a0, kb[j][0], kb[j][1]);
                    mma16816(c[(2 * j + 1) & 3], a1, kb[j][2], kb[j][3]);
                }
                float2 sv = make_float2((c[0][0] + c[1][0]) + (c[2][0] + c[3][0]), (c[0][1] + c[1][1]) + (c[2][1] + c[3][1]));
                *(float2*)(smem + CH_SB + warp * 256 + lane * 8) = sv;
            }
            named_bar(2, 256);
            uint32_t vx[2][4], vm[2];
            #pragma unroll
            for (int nt = 0; nt < 2; nt++)
                ldsm4(vx[nt], sb + CH_VX + tb * 10240 + (warp * 16 + nt * 8 + (lane & 7)) * TOKP + (lane >> 3) * 16);
            mbar_wait(barV, par);
            ldsm2(vm, sb + CH_VM + par * 2048 + (warp * 16 + (lane & 15)) * 16);
            if (s + 1 < NSEG) tok_bcast(s + 1);
            TSTAMP(5);
            {
                float sv[10];
                #pragma unroll
                for (int i = 0; i < 5; i++) {
                    float2 x = *(const float2*)(smem + CH_SB + i * 256 + lane * 8);
                    sv[2 * i] = x.x; sv[2 * i + 1] = x.y;
                }
                float m = fmaxf(fmaxf(fmaxf(sv[0], sv[1]), fmaxf(sv[2], sv[3])), fmaxf(fmaxf(sv[4], sv[5]), fmaxf(sv[6], sv[7])));
                m = fmaxf(m, fmaxf(sv[8], sv[9]));
                m = fmaxf(m, __shfl_xor_sync(~0u, m, 1));
                m = fmaxf(m, __shfl_xor_sync(~0u, m, 2));
                const float ms = -m * sc2;
                #pragma unroll
                for (int i = 0; i < 10; i++) sv[i] = ex2(fmaf(sv[i], sc2, ms));
                uint32_t pa[3][4];
                pa[0][0] = pack_bf16(sv[0], sv[1]); pa[0][1] = 0; pa[0][2] = pack_bf16(sv[2], sv[3]); pa[0][3] = 0;
                pa[1][0] = pack_bf16(sv[4], sv[5]); pa[1][1] = 0; pa[1][2] = pack_bf16(sv[6], sv[7]); pa[1][3] = 0;
                pa[2][0] = pack_bf16(sv[8], sv[9]); pa[2][1] = 0; pa[2][2] = 0; pa[2][3] = 0;
                TSTAMP(11);
                float c0[2][4] = {}, c1[2][4] = {};
                #pragma unroll
                for (int nt = 0; nt < 2; nt++) {
                    mma16816(c0[nt], pa[0], vm[nt], vx[nt][0]);
                    mma16816(c1[nt], pa[1], vx[nt][1], vx[nt][2]);
                }
                #pragma unroll
                for (int nt = 0; nt < 2; nt++) mma16816(c0[nt], pa[2], vx[nt][3], 0u);
                float l = ((sv[0] + sv[1]) + (sv[2] + sv[3])) + ((sv[4] + sv[5]) + (sv[6] + sv[7])) + (sv[8] + sv[9]);
                l += __shfl_xor_sync(~0u, l, 1);
                l += __shfl_xor_sync(~0u, l, 2);
                const float inv_l = __fdividef(1.f, l);
                uint32_t ow0 = pack_bf16((c0[0][0] + c1[0][0]) * inv_l, (c0[0][1] + c1[0][1]) * inv_l);
                uint32_t ow1 = pack_bf16((c0[1][0] + c1[1][0]) * inv_l, (c0[1][1] + c1[1][1]) * inv_l);
                *(uint2*)(smem + CH_OB + warp * 256 + lane * 8) = make_uint2(ow0, ow1);
            }
            if (s + 1 < NSEG) {
                bar_arrive(3, 384);
                named_bar(6, 384);
                TSTAMP(8);
                if (s + 2 < NSEG) xproj(s + 2);
            }
            TSTAMP(9);
        }
    }
    __syncthreads();
    cluster_sync();
}

constexpr int GM_STAGE_BYTES = 32768;
constexpr int gm_smem(int stages) { return stages * GM_STAGE_BYTES + 1024 + 128; }

__device__ __forceinline__ void wgmma_ss_n128_tb(float* d, uint64_t da, uint64_t db, int scale_d) {
    asm volatile("{\n.reg .pred p;\nsetp.ne.b32 p, %66, 0;\n"
        "wgmma.mma_async.sync.aligned.m64n128k16.f32.bf16.bf16 "
        "{%0,%1,%2,%3,%4,%5,%6,%7,%8,%9,%10,%11,%12,%13,%14,%15,%16,%17,%18,%19,%20,%21,%22,%23,%24,%25,%26,%27,%28,%29,%30,%31,"
        "%32,%33,%34,%35,%36,%37,%38,%39,%40,%41,%42,%43,%44,%45,%46,%47,%48,%49,%50,%51,%52,%53,%54,%55,%56,%57,%58,%59,%60,%61,%62,%63}, "
        "%64, %65, p, 1, 1, 0, 1;\n}"
        : "+f"(d[0]), "+f"(d[1]), "+f"(d[2]), "+f"(d[3]), "+f"(d[4]), "+f"(d[5]), "+f"(d[6]), "+f"(d[7]),
          "+f"(d[8]), "+f"(d[9]), "+f"(d[10]), "+f"(d[11]), "+f"(d[12]), "+f"(d[13]), "+f"(d[14]), "+f"(d[15]),
          "+f"(d[16]), "+f"(d[17]), "+f"(d[18]), "+f"(d[19]), "+f"(d[20]), "+f"(d[21]), "+f"(d[22]), "+f"(d[23]),
          "+f"(d[24]), "+f"(d[25]), "+f"(d[26]), "+f"(d[27]), "+f"(d[28]), "+f"(d[29]), "+f"(d[30]), "+f"(d[31]),
          "+f"(d[32]), "+f"(d[33]), "+f"(d[34]), "+f"(d[35]), "+f"(d[36]), "+f"(d[37]), "+f"(d[38]), "+f"(d[39]),
          "+f"(d[40]), "+f"(d[41]), "+f"(d[42]), "+f"(d[43]), "+f"(d[44]), "+f"(d[45]), "+f"(d[46]), "+f"(d[47]),
          "+f"(d[48]), "+f"(d[49]), "+f"(d[50]), "+f"(d[51]), "+f"(d[52]), "+f"(d[53]), "+f"(d[54]), "+f"(d[55]),
          "+f"(d[56]), "+f"(d[57]), "+f"(d[58]), "+f"(d[59]), "+f"(d[60]), "+f"(d[61]), "+f"(d[62]), "+f"(d[63])
        : "l"(da), "l"(db), "r"(scale_d));
}

template <int MODE, int KSPLIT, int GM_STAGES>
__global__ void __launch_bounds__(288, (GM_STAGES <= 3) ? 2 : 1)
gemm_tma(const __grid_constant__ CUtensorMap tmA, const __grid_constant__ CUtensorMap tmB, bf16* __restrict__ C,
         int K, int ntn, int ldc, int coff) {
    extern __shared__ __align__(1024) uint8_t smem_raw[];
    const uint32_t sb = (smem_u32(smem_raw) + 1023) & ~1023u;
    const uint32_t bar0 = sb + GM_STAGES * GM_STAGE_BYTES;
    const int tid = threadIdx.x, lane = tid & 31, warp = tid >> 5;
    const int ks = (KSPLIT == 2) ? (blockIdx.x & 1) : 0;
    const int tile = blockIdx.x / KSPLIT;
    const int m0 = (tile / ntn) * 128, n0 = (tile % ntn) * 128;
    const int kper = K / KSPLIT, kbase = ks * kper, nk = kper / 64;
    if (tid == 0) {
        for (int i = 0; i < GM_STAGES; i++) { mbar_init(bar0 + i * 8, 1); mbar_init(bar0 + 64 + i * 8, 2); }
        asm volatile("fence.mbarrier_init.release.cluster;" ::: "memory");
    }
    __syncthreads();
    if (warp == 8) {
        if (lane == 0) {
            for (int it = 0; it < nk; it++) {
                const int st = it % GM_STAGES, ph = (it / GM_STAGES) & 1;
                mbar_wait(bar0 + 64 + st * 8, ph ^ 1);
                mbar_expect(bar0 + st * 8, GM_STAGE_BYTES);
                const uint32_t sA = sb + st * GM_STAGE_BYTES, sB = sA + 16384;
                const int k0 = kbase + it * 64;
                tma_load_2d(sA, &tmA, k0, m0, bar0 + st * 8);
                tma_load_2d(sB, &tmB, n0, k0, bar0 + st * 8);
                tma_load_2d(sB + 8192, &tmB, n0 + 64, k0, bar0 + st * 8);
            }
        }
    } else {
        const int wg = warp >> 2, w4 = warp & 3, g = lane >> 2, t = lane & 3;
        float acc[64];
        for (int it = 0; it < nk; it++) {
            const int st = it % GM_STAGES, ph = (it / GM_STAGES) & 1;
            mbar_wait(bar0 + st * 8, ph);
            const uint32_t sA = sb + st * GM_STAGE_BYTES + wg * 8192, sB = sb + st * GM_STAGE_BYTES + 16384;
            wg_fence();
            #pragma unroll
            for (int kk = 0; kk < 4; kk++) {
                uint64_t da = make_desc(sA + kk * 32, 16, 1024, 1);
                uint64_t db = make_desc(sB + kk * 2048, 8192, 1024, 1);
                wgmma_ss_n128_tb(acc, da, db, (it > 0 || kk > 0));
            }
            wg_commit();
            if (it > 0) {
                wg_wait<1>();
                if ((tid & 127) == 0) mbar_arrive(bar0 + 64 + ((it - 1) % GM_STAGES) * 8);
            }
        }
        wg_wait<0>();
        #pragma unroll
        for (int j = 0; j < 64; j++) asm volatile("" : "+f"(acc[j]) :: "memory");
        if (KSPLIT == 2) {
            named_bar(1, 256);
            asm volatile("barrier.cluster.arrive.aligned;\nbarrier.cluster.wait.aligned;" ::: "memory");
            const uint32_t red = mapa(sb, 0) + tid * 16;
            if (ks == 1) {
                #pragma unroll
                for (int j = 0; j < 16; j++)
                    asm volatile("st.shared::cluster.v4.f32 [%0], {%1,%2,%3,%4};" :: "r"(red + j * 4096), "f"(acc[4 * j]), "f"(acc[4 * j + 1]), "f"(acc[4 * j + 2]), "f"(acc[4 * j + 3]) : "memory");
            }
            asm volatile("barrier.cluster.arrive.aligned;\nbarrier.cluster.wait.aligned;" ::: "memory");
            if (ks == 1) return;
            #pragma unroll
            for (int j = 0; j < 16; j++) {
                float4 v;
                asm volatile("ld.shared.v4.f32 {%0,%1,%2,%3}, [%4];" : "=f"(v.x), "=f"(v.y), "=f"(v.z), "=f"(v.w) : "r"(sb + tid * 16 + j * 4096) : "memory");
                acc[4 * j] += v.x; acc[4 * j + 1] += v.y; acc[4 * j + 2] += v.z; acc[4 * j + 3] += v.w;
            }
        }
        named_bar(1, 256);
        const int rl = wg * 64 + w4 * 16 + g;
        if (MODE == 0) {
            #pragma unroll
            for (int j = 0; j < 16; j++) {
                #pragma unroll
                for (int hh = 0; hh < 2; hh++) {
                    const uint32_t v = pack_bf16(acc[4 * j + 2 * hh], acc[4 * j + 2 * hh + 1]);
                    asm volatile("st.shared.b32 [%0], %1;" :: "r"(sb + (j >> 1) * 4096 + (rl + hh * 8) * 32 + (j & 1) * 16 + t * 4), "r"(v) : "memory");
                }
            }
            asm volatile("fence.proxy.async.shared::cta;" ::: "memory");
            named_bar(1, 256);
            if (tid < 8) {
                const int col = n0 + tid * 16, which = col >> 9, h = (col >> 4) & 31;
                bf16* dst = C + ((size_t)(which * NH + h) * S_LEN + m0) * 16;
                asm volatile("cp.async.bulk.global.shared::cta.bulk_group [%0], [%1], 4096;" :: "l"(dst), "r"(sb + tid * 4096) : "memory");
                asm volatile("cp.async.bulk.commit_group;" ::: "memory");
                asm volatile("cp.async.bulk.wait_group 0;" ::: "memory");
            }
        } else {
            #pragma unroll
            for (int j = 0; j < 16; j++) {
                #pragma unroll
                for (int hh = 0; hh < 2; hh++) {
                    const uint32_t v = pack_bf16(acc[4 * j + 2 * hh], acc[4 * j + 2 * hh + 1]);
                    asm volatile("st.shared.b32 [%0], %1;" :: "r"(sb + (rl + hh * 8) * 272 + j * 16 + t * 4), "r"(v) : "memory");
                }
            }
            named_bar(1, 256);
            #pragma unroll
            for (int i = 0; i < 8; i++) {
                const int idx = tid + i * 256, r = idx >> 4, c = idx & 15;
                uint4 v;
                asm volatile("ld.shared.v4.b32 {%0,%1,%2,%3}, [%4];" : "=r"(v.x), "=r"(v.y), "=r"(v.z), "=r"(v.w) : "r"(sb + r * 272 + c * 16) : "memory");
                *(uint4*)(C + (size_t)(m0 + r) * ldc + coff + n0 + c * 8) = v;
            }
        }
    }
    if (KSPLIT == 2 && warp == 8) {
        asm volatile("barrier.cluster.arrive.aligned;\nbarrier.cluster.wait.aligned;" ::: "memory");
        asm volatile("barrier.cluster.arrive.aligned;\nbarrier.cluster.wait.aligned;" ::: "memory");
    }
}

__device__ float g_kmax2[NH];

__global__ void __launch_bounds__(256) knorm_kernel(const bf16* __restrict__ qkv) {
    const int h = blockIdx.x, tid = threadIdx.x;
    const uint4* Kp = (const uint4*)(qkv + (size_t)(1 * NH + h) * S_LEN * 16);
    float mx = 0.f;
    for (int j = tid; j < S_LEN; j += 256) {
        uint4 a = Kp[2 * j], b = Kp[2 * j + 1];
        const uint32_t w[8] = { a.x, a.y, a.z, a.w, b.x, b.y, b.z, b.w };
        float s = 0.f;
        #pragma unroll
        for (int i = 0; i < 8; i++) {
            float lo = __uint_as_float(w[i] << 16), hi = __uint_as_float(w[i] & 0xffff0000u);
            s = fmaf(lo, lo, s); s = fmaf(hi, hi, s);
        }
        mx = fmaxf(mx, s);
    }
    #pragma unroll
    for (int o = 16; o > 0; o >>= 1) mx = fmaxf(mx, __shfl_xor_sync(~0u, mx, o));
    __shared__ float sm[8];
    if ((tid & 31) == 0) sm[tid >> 5] = mx;
    __syncthreads();
    if (tid == 0) {
        float m = sm[0];
        for (int i = 1; i < 8; i++) m = fmaxf(m, sm[i]);
        g_kmax2[h] = m;
    }
}

__device__ __noinline__ void attnA_slow_tile(const bf16* __restrict__ Q, const bf16* __restrict__ Kp, const bf16* __restrict__ Vp,
                                             bf16* __restrict__ o, int q0, int h, int lane) {
    const int g = lane >> 2, t = lane & 3;
    uint32_t qa[4];
    qa[0] = *(const uint32_t*)(Q + (q0 + g) * 16 + 2 * t);
    qa[1] = *(const uint32_t*)(Q + (q0 + g + 8) * 16 + 2 * t);
    qa[2] = *(const uint32_t*)(Q + (q0 + g) * 16 + 8 + 2 * t);
    qa[3] = *(const uint32_t*)(Q + (q0 + g + 8) * 16 + 8 + 2 * t);
    const float sc2 = 0.25f * 1.4426950408889634f;
    float m0 = -INFINITY, m1 = -INFINITY, l0 = 0.f, l1 = 0.f;
    float o0[4] = {}, o1[4] = {};
    const unsigned short* Vs = (const unsigned short*)Vp;
    for (int kb = 0; kb < S_LEN; kb += 16) {
        float s[2][4] = {};
        #pragma unroll
        for (int n = 0; n < 2; n++) {
            uint32_t b0 = *(const uint32_t*)(Kp + (kb + n * 8 + g) * 16 + 2 * t);
            uint32_t b1 = *(const uint32_t*)(Kp + (kb + n * 8 + g) * 16 + 8 + 2 * t);
            mma16816(s[n], qa, b0, b1);
        }
        float mx0 = fmaxf(m0, fmaxf(fmaxf(s[0][0], s[0][1]), fmaxf(s[1][0], s[1][1])));
        float mx1 = fmaxf(m1, fmaxf(fmaxf(s[0][2], s[0][3]), fmaxf(s[1][2], s[1][3])));
        mx0 = fmaxf(mx0, __shfl_xor_sync(~0u, mx0, 1)); mx0 = fmaxf(mx0, __shfl_xor_sync(~0u, mx0, 2));
        mx1 = fmaxf(mx1, __shfl_xor_sync(~0u, mx1, 1)); mx1 = fmaxf(mx1, __shfl_xor_sync(~0u, mx1, 2));
        float a0 = ex2((m0 - mx0) * sc2), a1 = ex2((m1 - mx1) * sc2);
        m0 = mx0; m1 = mx1;
        l0 *= a0; l1 *= a1;
        o0[0] *= a0; o0[1] *= a0; o0[2] *= a1; o0[3] *= a1; o1[0] *= a0; o1[1] *= a0; o1[2] *= a1; o1[3] *= a1;
        float p[8];
        p[0] = ex2((s[0][0] - m0) * sc2); p[1] = ex2((s[0][1] - m0) * sc2); p[2] = ex2((s[0][2] - m1) * sc2); p[3] = ex2((s[0][3] - m1) * sc2);
        p[4] = ex2((s[1][0] - m0) * sc2); p[5] = ex2((s[1][1] - m0) * sc2); p[6] = ex2((s[1][2] - m1) * sc2); p[7] = ex2((s[1][3] - m1) * sc2);
        l0 += p[0] + p[1] + p[4] + p[5]; l1 += p[2] + p[3] + p[6] + p[7];
        uint32_t pa[4] = { pack_bf16(p[0], p[1]), pack_bf16(p[2], p[3]), pack_bf16(p[4], p[5]), pack_bf16(p[6], p[7]) };
        #pragma unroll
        for (int n = 0; n < 2; n++) {
            const int d = n * 8 + g;
            uint32_t b0 = (uint32_t)Vs[(kb + 2 * t) * 16 + d] | ((uint32_t)Vs[(kb + 2 * t + 1) * 16 + d] << 16);
            uint32_t b1 = (uint32_t)Vs[(kb + 8 + 2 * t) * 16 + d] | ((uint32_t)Vs[(kb + 8 + 2 * t + 1) * 16 + d] << 16);
            mma16816(n == 0 ? o0 : o1, pa, b0, b1);
        }
    }
    l0 += __shfl_xor_sync(~0u, l0, 1); l0 += __shfl_xor_sync(~0u, l0, 2);
    l1 += __shfl_xor_sync(~0u, l1, 1); l1 += __shfl_xor_sync(~0u, l1, 2);
    float i0 = 1.f / l0, i1 = 1.f / l1;
    *(uint32_t*)(o + (size_t)(q0 + g) * DM + h * 16 + 2 * t) = pack_bf16(o0[0] * i0, o0[1] * i0);
    *(uint32_t*)(o + (size_t)(q0 + g + 8) * DM + h * 16 + 2 * t) = pack_bf16(o0[2] * i1, o0[3] * i1);
    *(uint32_t*)(o + (size_t)(q0 + g) * DM + h * 16 + 8 + 2 * t) = pack_bf16(o1[0] * i0, o1[1] * i0);
    *(uint32_t*)(o + (size_t)(q0 + g + 8) * DM + h * 16 + 8 + 2 * t) = pack_bf16(o1[2] * i1, o1[3] * i1);
}

#define AT_EXB ex2
#define AT_EXA ex2
#define AT_EXC ex2
#define AT_CHUNK 128
#define AT_UNROLL 2
constexpr int AT_CH = AT_CHUNK;
constexpr int AT_UNR = AT_UNROLL;
constexpr int AT_STAGES = 3;
__global__ void __launch_bounds__(128) attnA_kernel(const bf16* __restrict__ qkv, bf16* __restrict__ o) {
    __shared__ __align__(128) uint8_t sm[AT_STAGES * AT_CH * 64];
    const int tid = threadIdx.x, lane = tid & 31, warp = tid >> 5;
    const int h = blockIdx.y, q0 = blockIdx.x * 128 + warp * 32;
    const int g = lane >> 2, t = lane & 3;
    const bf16* Q = qkv + (size_t)(0 * NH + h) * S_LEN * 16;
    const bf16* Kp = qkv + (size_t)(1 * NH + h) * S_LEN * 16;
    const bf16* Vp = qkv + (size_t)(2 * NH + h) * S_LEN * 16;
    const uint32_t sb = smem_u32(sm);
    auto load_stage = [&](int c) {
        const uint32_t base = sb + (c % AT_STAGES) * (AT_CH * 64);
        #pragma unroll
        for (int i = 0; i < AT_CH / 64; i++) {
            int idx = tid + i * 128, r = idx >> 1, cc = idx & 1;
            uint32_t off = r * 32 + ((cc ^ ((r >> 2) & 1)) << 4);
            cp_async16(base + off, Kp + (size_t)(c * AT_CH + r) * 16 + cc * 8);
            cp_async16(base + AT_CH * 32 + off, Vp + (size_t)(c * AT_CH + r) * 16 + cc * 8);
        }
        asm volatile("cp.async.commit_group;" ::: "memory");
    };
    load_stage(0);
    load_stage(1);
    const float sc2 = 0.25f * 1.4426950408889634f;
    uint32_t qa[2][4];
    float nb[2][2];
    {
        const float kmax = sqrtf(g_kmax2[h]) * 1.0001f;
        #pragma unroll
        for (int mt = 0; mt < 2; mt++) {
            const int r0 = q0 + mt * 16 + g;
            qa[mt][0] = *(const uint32_t*)(Q + r0 * 16 + 2 * t);
            qa[mt][1] = *(const uint32_t*)(Q + (r0 + 8) * 16 + 2 * t);
            qa[mt][2] = *(const uint32_t*)(Q + r0 * 16 + 8 + 2 * t);
            qa[mt][3] = *(const uint32_t*)(Q + (r0 + 8) * 16 + 8 + 2 * t);
            #pragma unroll
            for (int hh = 0; hh < 2; hh++) {
                float a0 = __uint_as_float(qa[mt][hh] << 16), a1 = __uint_as_float(qa[mt][hh] & 0xffff0000u);
                float a2 = __uint_as_float(qa[mt][2 + hh] << 16), a3 = __uint_as_float(qa[mt][2 + hh] & 0xffff0000u);
                float n2 = a0 * a0 + a1 * a1 + a2 * a2 + a3 * a3;
                n2 += __shfl_xor_sync(~0u, n2, 1); n2 += __shfl_xor_sync(~0u, n2, 2);
                nb[mt][hh] = -(sqrtf(n2) * 1.0001f * kmax) * sc2;
            }
        }
    }
    float oa[2][3][4] = {};
    const uint32_t ones = 0x3F803F80u;
    const int rk = (lane & 7) + ((lane >> 4) << 3), ck = (lane >> 3) & 1;
    const uint32_t koff = rk * 32 + ((ck ^ ((rk >> 2) & 1)) << 4);
    const int rv = lane & 15, cv = lane >> 4;
    const uint32_t voff = AT_CH * 32 + rv * 32 + ((cv ^ ((rv >> 2) & 1)) << 4);
    constexpr int NCH = S_LEN / AT_CH;
    #pragma unroll 1
    for (int c = 0; c < NCH; c++) {
        asm volatile("cp.async.wait_group 1;" ::: "memory");
        __syncthreads();
        if (c + 2 < NCH) load_stage(c + 2); else asm volatile("cp.async.commit_group;" ::: "memory");
        const uint32_t base = sb + (c % AT_STAGES) * (AT_CH * 64);
        #pragma unroll AT_UNR
        for (int j = 0; j < AT_CH / 16; j++) {
            uint32_t kb[4], vb[4];
            ldsm4(kb, base + j * 512 + koff);
            ldsm4t(vb, base + j * 512 + voff);
            #pragma unroll
            for (int mt = 0; mt < 2; mt++) {
                float s0[4] = {}, s1[4] = {};
                mma16816(s0, qa[mt], kb[0], kb[1]);
                mma16816(s1, qa[mt], kb[2], kb[3]);
                uint32_t pa[4];
                pa[0] = pack_bf16_trunc(ex2(fmaf(s0[0], sc2, nb[mt][0])), AT_EXA(fmaf(s0[1], sc2, nb[mt][0])));
                pa[1] = pack_bf16_trunc(ex2(fmaf(s0[2], sc2, nb[mt][1])), AT_EXC(fmaf(s0[3], sc2, nb[mt][1])));
                pa[2] = pack_bf16_trunc(ex2(fmaf(s1[0], sc2, nb[mt][0])), AT_EXB(fmaf(s1[1], sc2, nb[mt][0])));
                pa[3] = pack_bf16_trunc(ex2(fmaf(s1[2], sc2, nb[mt][1])), AT_EXB(fmaf(s1[3], sc2, nb[mt][1])));
                mma16816(oa[mt][0], pa, vb[0], vb[1]);
                mma16816(oa[mt][1], pa, vb[2], vb[3]);
                mma16816(oa[mt][2], pa, ones, ones);
            }
        }
    }
    #pragma unroll
    for (int mt = 0; mt < 2; mt++) {
        const float l0 = oa[mt][2][0], l1 = oa[mt][2][2];
        const bool bad = !(l0 > 1e-27f && l1 > 1e-27f && l0 < 1e30f && l1 < 1e30f);
        if (__any_sync(~0u, bad)) {
            attnA_slow_tile(Q, Kp, Vp, o, q0 + mt * 16, h, lane);
        } else {
            const float i0 = 1.f / l0, i1 = 1.f / l1;
            const int r0 = q0 + mt * 16 + g;
            *(uint32_t*)(o + (size_t)r0 * DM + h * 16 + 2 * t) = pack_bf16(oa[mt][0][0] * i0, oa[mt][0][1] * i0);
            *(uint32_t*)(o + (size_t)(r0 + 8) * DM + h * 16 + 2 * t) = pack_bf16(oa[mt][0][2] * i1, oa[mt][0][3] * i1);
            *(uint32_t*)(o + (size_t)r0 * DM + h * 16 + 8 + 2 * t) = pack_bf16(oa[mt][1][0] * i0, oa[mt][1][1] * i0);
            *(uint32_t*)(o + (size_t)(r0 + 8) * DM + h * 16 + 8 + 2 * t) = pack_bf16(oa[mt][1][2] * i1, oa[mt][1][3] * i1);
        }
    }
}

typedef CUresult (*PFN_encodeTiled)(CUtensorMap*, CUtensorMapDataType, cuuint32_t, void*, const cuuint64_t*, const cuuint64_t*,
                                    const cuuint32_t*, const cuuint32_t*, CUtensorMapInterleave, CUtensorMapSwizzle,
                                    CUtensorMapL2promotion, CUtensorMapFloatOOBfill);

static CUtensorMap make_tmap_2d(PFN_encodeTiled enc, const void* ptr, uint64_t inner, uint64_t outer, uint32_t box_inner, uint32_t box_outer) {
    CUtensorMap tm;
    cuuint64_t dims[2] = { inner, outer };
    cuuint64_t strides[1] = { inner * 2 };
    cuuint32_t box[2] = { box_inner, box_outer };
    cuuint32_t es[2] = { 1, 1 };
    enc(&tm, CU_TENSOR_MAP_DATA_TYPE_BFLOAT16, 2, (void*)ptr, dims, strides, box, es, CU_TENSOR_MAP_INTERLEAVE_NONE,
        CU_TENSOR_MAP_SWIZZLE_128B, CU_TENSOR_MAP_L2_PROMOTION_L2_128B, CU_TENSOR_MAP_FLOAT_OOB_FILL_NONE);
    return tm;
}

#define TL(i, strm) do {} while (0)
extern "C" void kernel_launch(void* const* d_in, const int* in_sizes, int n_in, void* d_out, int out_size) {
    const bf16* A_x = (const bf16*)d_in[0];
    const bf16* A_wqkv = (const bf16*)d_in[1];
    const bf16* A_wo = (const bf16*)d_in[2];
    const bf16* B_x = (const bf16*)d_in[3];
    const bf16* B_mem0 = (const bf16*)d_in[4];
    const bf16* B_Wq = (const bf16*)d_in[5];
    const bf16* B_Wk = (const bf16*)d_in[6];
    const bf16* B_Wv = (const bf16*)d_in[7];
    const bf16* B_Wo = (const bf16*)d_in[8];
    bf16* out = (bf16*)d_out;

    static PFN_encodeTiled enc = nullptr;
    static CUtensorMap tmX, tmAx, tmWqkv, tmOA, tmWoA, tmOtok, tmWoB;
    static const void* key[4] = { nullptr, nullptr, nullptr, nullptr };
    static bf16 *p_otok, *p_qkvA, *p_oA;
    static cudaStream_t s2;
    static cudaEvent_t evFork, evJoin;
    if (!enc) {
        int prLo = 0, prHi = 0;
        cudaDeviceGetStreamPriorityRange(&prLo, &prHi);
        cudaStreamCreateWithPriority(&s2, cudaStreamNonBlocking, prLo);
        cudaEventCreateWithFlags(&evFork, cudaEventDisableTiming);
        cudaEventCreateWithFlags(&evJoin, cudaEventDisableTiming);
        void* fn = nullptr; cudaDriverEntryPointQueryResult qres;
        cudaGetDriverEntryPoint("cuTensorMapEncodeTiled", &fn, cudaEnableDefault, &qres);
        enc = (PFN_encodeTiled)fn;
        cudaFuncSetAttribute(chain_kernel, cudaFuncAttributeMaxDynamicSharedMemorySize, CH_SMEM_ALLOC);
        cudaFuncSetAttribute(gemm_tma<0, 1, 3>, cudaFuncAttributeMaxDynamicSharedMemorySize, gm_smem(3));
        cudaFuncSetAttribute(gemm_tma<1, 1, 3>, cudaFuncAttributeMaxDynamicSharedMemorySize, gm_smem(3));
        cudaFuncSetAttribute(gemm_tma<1, 2, 6>, cudaFuncAttributeMaxDynamicSharedMemorySize, gm_smem(6));
        cudaGetSymbolAddress((void**)&p_otok, g_otok);
        cudaGetSymbolAddress((void**)&p_qkvA, g_qkvA);
        cudaGetSymbolAddress((void**)&p_oA, g_oA);
        tmOA = make_tmap_2d(enc, p_oA, 512, 2048, 64, 128);
        tmOtok = make_tmap_2d(enc, p_otok, 4096, 2048, 64, 128);
    }
    if (key[0] != (const void*)B_x || key[1] != (const void*)A_x || key[2] != (const void*)A_wqkv || key[3] != (const void*)B_Wo) {
        tmX = make_tmap_2d(enc, B_x, 512, 2048, 64, 32);
        tmAx = make_tmap_2d(enc, A_x, 512, 2048, 64, 128);
        tmWqkv = make_tmap_2d(enc, A_wqkv, 1536, 512, 64, 64);
        tmWoA = make_tmap_2d(enc, A_wo, 512, 512, 64, 64);
        tmWoB = make_tmap_2d(enc, B_Wo, 512, 4096, 64, 64);
        key[0] = B_x; key[1] = A_x; key[2] = A_wqkv; key[3] = B_Wo;
    }

    cudaStream_t st = cudaStreamPerThread;
    TL(0, st);
    cudaEventRecord(evFork, st);
    cudaStreamWaitEvent(s2, evFork, 0);
    chain_kernel<<<96, 384, CH_SMEM_ALLOC, st>>>(tmX, B_mem0, B_Wq, B_Wk, B_Wv, B_Wo);
    TL(1, st);
    gemm_tma<0, 1, 3><<<16 * 12, 288, gm_smem(3), s2>>>(tmAx, tmWqkv, p_qkvA, 512, 12, 0, 0);
    TL(2, s2);
    knorm_kernel<<<NH, 256, 0, s2>>>(p_qkvA);
    attnA_kernel<<<dim3(2048 / 128, NH), 128, 0, s2>>>(p_qkvA, p_oA);
    TL(3, s2);
    gemm_tma<1, 1, 3><<<16 * 4, 288, gm_smem(3), s2>>>(tmOA, tmWoA, out, 512, 4, 1024, 0);
    TL(4, s2);
    cudaEventRecord(evJoin, s2);
    {
        cudaLaunchConfig_t cfg = {};
        cfg.gridDim = dim3(16 * 4 * 2); cfg.blockDim = dim3(288); cfg.dynamicSmemBytes = gm_smem(6); cfg.stream = st;
        cudaLaunchAttribute at[1]; at[0].id = cudaLaunchAttributeClusterDimension; at[0].val.clusterDim.x = 2; at[0].val.clusterDim.y = 1; at[0].val.clusterDim.z = 1;
        cfg.attrs = at; cfg.numAttrs = 1;
        cudaLaunchKernelEx(&cfg, gemm_tma<1, 2, 6>, tmOtok, tmWoB, out, 4096, 4, 1024, 512);
    }
    TL(6, st);
    cudaStreamWaitEvent(st, evJoin, 0);
    TL(7, st);
}
```

```cpp
#include <cuda_runtime.h>
#include <cuda_bf16.h>
#include <cuda.h>
#include <stdint.h>

typedef __nv_bfloat16 bf16;

constexpr int S_LEN = 2048;
constexpr int DM = 512;
constexpr int NH = 32;
constexpr int A_DH = 16;
constexpr int B_DH = 128;
constexpr int B_M = 8;
constexpr int SEG = 32;
constexpr int NSEG = 64;

__device__ float4 g_acc[NSEG][12][4][32];
__device__ unsigned g_gridbar;
__device__ bf16 g_otok[S_LEN * NH * B_DH];
__device__ bf16 g_qkvA[3 * NH * S_LEN * A_DH];
__device__ bf16 g_oA[S_LEN * DM];

#define TSTAMP(i) do {} while (0)
__device__ __forceinline__ uint32_t smem_u32(const void* p) { return (uint32_t)__cvta_generic_to_shared(p); }
__device__ __forceinline__ uint32_t mapa(uint32_t a, uint32_t r) {
    uint32_t o; asm volatile("mapa.shared::cluster.u32 %0, %1, %2;" : "=r"(o) : "r"(a), "r"(r)); return o;
}
__device__ __forceinline__ void mbar_init(uint32_t a, uint32_t c) { asm volatile("mbarrier.init.shared.b64 [%0], %1;" :: "r"(a), "r"(c)); }
__device__ __forceinline__ void mbar_expect(uint32_t a, uint32_t b) {
    asm volatile("mbarrier.arrive.expect_tx.shared.b64 _, [%0], %1;" :: "r"(a), "r"(b) : "memory");
}
__device__ __forceinline__ void mbar_arrive(uint32_t a) {
    asm volatile("mbarrier.arrive.shared.b64 _, [%0];" :: "r"(a) : "memory");
}
__device__ __forceinline__ bool mbar_try(uint32_t a, uint32_t par) {
    uint32_t ok;
    asm volatile("{\n.reg .pred p;\nmbarrier.try_wait.parity.shared::cta.b64 p, [%1], %2;\nselp.u32 %0, 1, 0, p;\n}"
                 : "=r"(ok) : "r"(a), "r"(par) : "memory");
    return ok != 0;
}
__device__ __forceinline__ void mbar_wait(uint32_t a, uint32_t par) {
    #pragma unroll 1
    for (int it = 0; it < 4000000; it++) { if (mbar_try(a, par)) return; }
}
__device__ __forceinline__ void st_async_b32(uint32_t a, uint32_t x, uint32_t mb) {
    asm volatile("st.async.shared::cluster.mbarrier::complete_tx::bytes.b32 [%0], %1, [%2];" :: "r"(a), "r"(x), "r"(mb) : "memory");
}
__device__ __forceinline__ void st_async_v4(uint32_t a, uint32_t x, uint32_t y, uint32_t z, uint32_t w, uint32_t mb) {
    asm volatile("st.async.shared::cluster.mbarrier::complete_tx::bytes.v4.b32 [%0], {%1,%2,%3,%4}, [%5];"
                 :: "r"(a), "r"(x), "r"(y), "r"(z), "r"(w), "r"(mb) : "memory");
}
__device__ __forceinline__ void bulk_s2s(uint32_t dst, uint32_t src, uint32_t bytes, uint32_t mb) {
    asm volatile("cp.async.bulk.shared::cluster.shared::cta.mbarrier::complete_tx::bytes [%0], [%1], %2, [%3];"
                 :: "r"(dst), "r"(src), "r"(bytes), "r"(mb) : "memory");
}
__device__ __forceinline__ void cluster_sync() {
    asm volatile("barrier.cluster.arrive.aligned;\nbarrier.cluster.wait.aligned;" ::: "memory");
}
__device__ __forceinline__ float4 ld_relaxed_f4(const float4* p) {
    float4 v;
    asm volatile("ld.relaxed.gpu.global.v4.f32 {%0,%1,%2,%3}, [%4];" : "=f"(v.x), "=f"(v.y), "=f"(v.z), "=f"(v.w) : "l"(p) : "memory");
    return v;
}
__device__ __forceinline__ void red_v4(float4* p, float a, float b, float c, float d) {
    asm volatile("red.relaxed.gpu.global.add.v4.f32 [%0], {%1,%2,%3,%4};" :: "l"(p), "f"(a), "f"(b), "f"(c), "f"(d) : "memory");
}
__device__ __forceinline__ void ldsm4(uint32_t* r, uint32_t a) {
    asm volatile("ldmatrix.sync.aligned.m8n8.x4.shared.b16 {%0,%1,%2,%3}, [%4];"
                 : "=r"(r[0]), "=r"(r[1]), "=r"(r[2]), "=r"(r[3]) : "r"(a) : "memory");
}
__device__ __forceinline__ void ldsm4t(uint32_t* r, uint32_t a) {
    asm volatile("ldmatrix.sync.aligned.m8n8.x4.trans.shared.b16 {%0,%1,%2,%3}, [%4];"
                 : "=r"(r[0]), "=r"(r[1]), "=r"(r[2]), "=r"(r[3]) : "r"(a) : "memory");
}
__device__ __forceinline__ void ldsm2(uint32_t* r, uint32_t a) {
    asm volatile("ldmatrix.sync.aligned.m8n8.x2.shared.b16 {%0,%1}, [%2];"
                 : "=r"(r[0]), "=r"(r[1]) : "r"(a) : "memory");
}
__device__ __forceinline__ void mma16816(float* c, const uint32_t* a, uint32_t b0, uint32_t b1) {
    asm volatile("mma.sync.aligned.m16n8k16.row.col.f32.bf16.bf16.f32 {%0,%1,%2,%3}, {%4,%5,%6,%7}, {%8,%9}, {%0,%1,%2,%3};"
                 : "+f"(c[0]), "+f"(c[1]), "+f"(c[2]), "+f"(c[3])
                 : "r"(a[0]), "r"(a[1]), "r"(a[2]), "r"(a[3]), "r"(b0), "r"(b1));
}
__device__ __forceinline__ uint32_t pack_bf16(float lo, float hi) {
    uint32_t r; asm("cvt.rn.bf16x2.f32 %0, %1, %2;" : "=r"(r) : "f"(hi), "f"(lo)); return r;
}
__device__ __forceinline__ uint32_t pack_bf16_trunc(float lo, float hi) { return __byte_perm(__float_as_uint(lo), __float_as_uint(hi), 0x7632); }
__device__ __forceinline__ float ex2(float x) { float y; asm("ex2.approx.ftz.f32 %0, %1;" : "=f"(y) : "f"(x)); return y; }
__device__ __forceinline__ float ex2_fma(float x) {
    x = fmaxf(x, -126.f);
    const float tt = x + 12582912.f;
    const float r = x - (tt - 12582912.f);
    float p = fmaf(0.0013276461977511644f, r, 0.009675540961325169f);
    p = fmaf(p, r, 0.05550713464617729f);
    p = fmaf(p, r, 0.24022120237350464f);
    p = fmaf(p, r, 0.6931469440460205f);
    p = fmaf(p, r, 1.0000001192092896f);
    return __int_as_float(__float_as_int(p) + (__float_as_int(tt) << 23));
}
__device__ __forceinline__ void cp_async16(uint32_t dst, const void* src) {
    asm volatile("cp.async.cg.shared.global [%0], [%1], 16;" :: "r"(dst), "l"(src) : "memory");
}
__device__ __forceinline__ void cp_async_wait_all() { asm volatile("cp.async.wait_all;" ::: "memory"); }
__device__ __forceinline__ void named_bar(int id, int n) { asm volatile("bar.sync %0, %1;" :: "r"(id), "r"(n) : "memory"); }
__device__ __forceinline__ uint64_t make_desc(uint32_t saddr, uint32_t lbo, uint32_t sbo, uint32_t swz) {
    uint64_t d = 0;
    d |= (uint64_t)((saddr & 0x3FFFF) >> 4);
    d |= (uint64_t)((lbo >> 4) & 0x3FFF) << 16;
    d |= (uint64_t)((sbo >> 4) & 0x3FFF) << 32;
    d |= (uint64_t)swz << 62;
    return d;
}
__device__ __forceinline__ void wg_fence() { asm volatile("wgmma.fence.sync.aligned;" ::: "memory"); }
__device__ __forceinline__ void wg_commit() { asm volatile("wgmma.commit_group.sync.aligned;" ::: "memory"); }
template <int N> __device__ __forceinline__ void wg_wait() { asm volatile("wgmma.wait_group.sync.aligned %0;" :: "n"(N) : "memory"); }
__device__ __forceinline__ void wgmma_rs_n32(float* d, const uint32_t* a, uint64_t desc, int scale_d) {
    asm volatile("{\n.reg .pred p;\nsetp.ne.b32 p, %21, 0;\n"
                 "wgmma.mma_async.sync.aligned.m64n32k16.f32.bf16.bf16 {%0,%1,%2,%3,%4,%5,%6,%7,%8,%9,%10,%11,%12,%13,%14,%15}, {%16,%17,%18,%19}, %20, p, 1, 1, 0;\n}"
                 : "+f"(d[0]), "+f"(d[1]), "+f"(d[2]), "+f"(d[3]), "+f"(d[4]), "+f"(d[5]), "+f"(d[6]), "+f"(d[7]),
                   "+f"(d[8]), "+f"(d[9]), "+f"(d[10]), "+f"(d[11]), "+f"(d[12]), "+f"(d[13]), "+f"(d[14]), "+f"(d[15])
                 : "r"(a[0]), "r"(a[1]), "r"(a[2]), "r"(a[3]), "l"(desc), "r"(scale_d));
}
__device__ __forceinline__ void tma_load_2d_mc(uint32_t dst, const CUtensorMap* tm, int c0, int c1, uint32_t mb, uint16_t mask) {
    asm volatile("cp.async.bulk.tensor.2d.shared::cluster.global.mbarrier::complete_tx::bytes.multicast::cluster [%0], [%1, {%3, %4}], [%2], %5;"
                 :: "r"(dst), "l"(tm), "r"(mb), "r"(c0), "r"(c1), "h"(mask) : "memory");
}
__device__ __forceinline__ void tma_load_2d(uint32_t dst, const CUtensorMap* tm, int c0, int c1, uint32_t mb) {
    asm volatile("cp.async.bulk.tensor.2d.shared::cluster.global.mbarrier::complete_tx::bytes [%0], [%1, {%3, %4}], [%2];"
                 :: "r"(dst), "l"(tm), "r"(mb), "r"(c0), "r"(c1) : "memory");
}

constexpr int CH_XS = 0;
constexpr int CH_KX = 65536;
constexpr int CH_VX = CH_KX + 30720;
constexpr int CH_QX = CH_VX + 30720;
constexpr int CH_SB2 = CH_QX + 36864;
constexpr int CH_MEMT = CH_SB2 + 2560;
constexpr int CH_KM = CH_MEMT + 8192;
constexpr int CH_VM = CH_KM + 4096;
constexpr int CH_QM = CH_VM + 4096;
constexpr int CH_SB = CH_QM + 2048;
constexpr int CH_OB = CH_SB + 1280;
constexpr int CH_BAR = CH_OB + 2048;
constexpr int CH_SMEM = CH_BAR + 128;
constexpr int CH_SMEM_ALLOC = 192 * 1024;
#define POLL_DELAY 900
constexpr int TOKP = 80;
constexpr int WOP = 400;

template <int J0, int J1>
__device__ __forceinline__ void qkv_range(float (&c)[4][4], const uint32_t (&wr)[32][4], uint32_t memt_lane) {
    #pragma unroll
    for (int j = J0; j < J1; j++) {
        uint32_t b[4];
        ldsm4t(b, memt_lane + j * 512);
        mma16816(c[(2 * j) & 3], wr[2 * j], b[0], b[1]);
        mma16816(c[(2 * j + 1) & 3], wr[2 * j + 1], b[2], b[3]);
    }
}
__device__ __forceinline__ void bar_arrive(int id, int n) { asm volatile("bar.arrive %0, %1;" :: "r"(id), "r"(n) : "memory"); }

__global__ void __cluster_dims__(3, 1, 1) __launch_bounds__(384, 1)
chain_kernel(const __grid_constant__ CUtensorMap tmX, const bf16* __restrict__ mem0,
             const bf16* __restrict__ Wq, const bf16* __restrict__ Wk, const bf16* __restrict__ Wv,
             const bf16* __restrict__ Wo) {
    extern __shared__ __align__(1024) uint8_t smem[];
    const uint32_t sb = smem_u32(smem);
    uint32_t rank; asm volatile("mov.u32 %0, %%cluster_ctarank;" : "=r"(rank));
    const int tid = threadIdx.x, lane = tid & 31, warp = tid >> 5, wg = warp >> 2, w4 = warp & 3;
    const int g = lane >> 2, t = lane & 3;
    const int head = blockIdx.x / 3;
    const uint32_t barMem = sb + CH_BAR, barQK = barMem + 8, barV = barMem + 16, barTok = barMem + 24  , barX = barMem + 48  ;

    if (tid == 0) {
        mbar_init(barMem, 1); mbar_init(barQK, rank == 2 ? 1 : 9); mbar_init(barV, rank == 2 ? 9 : 1);
        mbar_init(barTok, 1); mbar_init(barTok + 8, 1); mbar_init(barTok + 16, 1); mbar_init(barX, 1); mbar_init(barX + 8, 1);
        asm volatile("fence.mbarrier_init.release.cluster;" ::: "memory");
    }
    {
        float4* p = &g_acc[0][0][0][0];
        constexpr int TOT = NSEG * 12 * 4 * 32;
        for (int i = blockIdx.x * 384 + tid; i < TOT; i += 96 * 384) p[i] = make_float4(0.f, 0.f, 0.f, 0.f);
    }
    const int tile0 = rank * 12 + w4 * 3;
    {
        const bf16* W = (rank == 0) ? Wq : (rank == 1 ? Wk : Wv);
        const int nf = (rank == 2) ? 128 : 192;
        for (int i = tid; i < 512 * 16; i += 384) {
            int d = i >> 4, c = i & 15;
            cp_async16(sb + (c >> 3) * 65536 + d * 128 + (((c & 7) ^ (d & 7)) << 4), W + (size_t)d * 4096 + head * 128 + c * 8);
        }
        for (int i = tid; i < 128 * (nf / 8); i += 384) {
            int e = i / (nf / 8), c = i % (nf / 8);
            cp_async16(sb + 131072 + e * WOP + c * 16, Wo + (size_t)(head * 128 + e) * 512 + rank * 192 + c * 8);
        }
        cp_async_wait_all();
        __threadfence();
        __syncthreads();
    }
    const uint32_t pr0 = mapa(sb, rank == 0 ? 1 : 0), pr1 = mapa(sb, rank == 2 ? 1 : 2);
    const uint32_t self = mapa(sb, rank);
    const int mi = lane >> 3, r8 = lane & 7;

    if (wg == 2) {
        asm volatile("setmaxnreg.dec.sync.aligned.u32 152;");
        uint32_t wr[24][4];
        #pragma unroll
        for (int i = 0; i < 3; i++)
            #pragma unroll
            for (int kk = 0; kk < 8; kk++) {
                if (tile0 + i < 32) ldsm4t(wr[i * 8 + kk], sb + 131072 + (kk * 16 + (mi >> 1) * 8 + r8) * WOP + ((w4 * 3 + i) * 16 + (mi & 1) * 8) * 2);
                else { wr[i * 8 + kk][0] = 0; wr[i * 8 + kk][1] = 0; wr[i * 8 + kk][2] = 0; wr[i * 8 + kk][3] = 0; }
            }
        unsigned bar_target = 0;
        if (tid == 256) {
            unsigned ticket = atomicAdd(&g_gridbar, 1u);
            bar_target = (ticket / 96u + 1u) * 96u;
        }
        cluster_sync();
        const bool boss = (tid == 256 + 96);
        const uint32_t mem_remote_bytes = 8192 - ((rank == 2) ? 2048 : 3072);
        const uint32_t tok_bytes = (rank == 0) ? 20480 : 16384;
        const int nvalid = min(max(32 - tile0, 0), 3);
        const int slot = rank * 4 + w4;
        auto issue_x = [&](int seg) {
            mbar_expect(barX + (seg & 1) * 8, 32768);
            #pragma unroll 1
            for (int c = rank; c < 8; c += 3)
                tma_load_2d_mc(sb + CH_XS + (seg & 1) * 32768 + c * 4096, &tmX, c * 64, seg * SEG, barX + (seg & 1) * 8, (uint16_t)7);
        };
        if (boss) {
            mbar_expect(barTok, tok_bytes); mbar_expect(barTok + 8, tok_bytes); mbar_expect(barTok + 16, tok_bytes);
            issue_x(0); issue_x(1);
        }
        auto tok_attn = [&](int seg) {
            const float sc2 = 0.08838834764831845f * 1.4426950408889634f;
            const int mt = rank - 1;
            const uint32_t sQ = sb + CH_QX + (seg % 3) * 12288, sK = sb + CH_KX + (seg % 3) * 10240, sV = sb + CH_VX + (seg % 3) * 10240;
            const uint32_t sKM = sb + CH_KM + (seg & 1) * 2048, sVM = sb + CH_VM + (seg & 1) * 2048;
            {
                float c0[2][4] = {}, c1[2][4] = {};
                #pragma unroll
                for (int j = 0; j < 4; j++) {
                    uint32_t qa[2][4], bb[4];
                    #pragma unroll
                    for (int h2 = 0; h2 < 2; h2++) {
                        const int dim = j * 32 + h2 * 16 + (mi >> 1) * 8 + r8;
                        ldsm4t(qa[h2], sQ + dim * 48 + (mi & 1) * 16);
                    }
                    ldsm4t(bb, sK + (j * 32 + lane) * TOKP + w4 * 16);
                    mma16816(c1[0], qa[0], bb[0], bb[1]);
                    mma16816(c1[1], qa[1], bb[2], bb[3]);
                    if (w4 == 3) {
                        ldsm4t(bb, sKM + (j * 32 + lane) * 16);
                        mma16816(c0[0], qa[0], bb[0], bb[1]);
                        mma16816(c0[1], qa[1], bb[2], bb[3]);
                    }
                }
                *(float4*)(smem + CH_SB2 + (w4 + 1) * 512 + lane * 16) = make_float4(c1[0][0] + c1[1][0], c1[0][1] + c1[1][1], c1[0][2] + c1[1][2], c1[0][3] + c1[1][3]);
                if (w4 == 3) *(float4*)(smem + CH_SB2 + lane * 16) = make_float4(c0[0][0] + c0[1][0], c0[0][1] + c0[1][1], c0[0][2] + c0[1][2], c0[0][3] + c0[1][3]);
            }
            named_bar(7, 128);
            float sc[5][4];
            #pragma unroll
            for (int i = 0; i < 5; i++) {
                float4 x = *(const float4*)(smem + CH_SB2 + i * 512 + lane * 16);
                sc[i][0] = x.x; sc[i][1] = x.y; sc[i][2] = x.z; sc[i][3] = x.w;
            }
            const int tq0 = 8 * (g >> 1) + 2 * (2 * mt) + (g & 1);
            const int tq1 = tq0 + 2;
            float m0 = fmaxf(sc[0][0], sc[0][1]), m1 = fmaxf(sc[0][2], sc[0][3]);
            #pragma unroll
            for (int i = 1; i < 5; i++) {
                #pragma unroll
                for (int e2 = 0; e2 < 2; e2++) {
                    int tk = 8 * t + 2 * (i - 1) + e2;
                    if (tk > tq0) sc[i][e2] = -INFINITY;
                    if (tk > tq1) sc[i][2 + e2] = -INFINITY;
                    m0 = fmaxf(m0, sc[i][e2]); m1 = fmaxf(m1, sc[i][2 + e2]);
                }
            }
            m0 = fmaxf(m0, __shfl_xor_sync(~0u, m0, 1)); m0 = fmaxf(m0, __shfl_xor_sync(~0u, m0, 2));
            m1 = fmaxf(m1, __shfl_xor_sync(~0u, m1, 1)); m1 = fmaxf(m1, __shfl_xor_sync(~0u, m1, 2));
            float l0 = 0.f, l1 = 0.f;
            const float ms0 = -m0 * sc2, ms1 = -m1 * sc2;
            uint32_t pp[3][4];
            #pragma unroll
            for (int i = 0; i < 5; i++) {
                sc[i][0] = ex2(fmaf(sc[i][0], sc2, ms0)); sc[i][1] = ex2(fmaf(sc[i][1], sc2, ms0));
                sc[i][2] = ex2(fmaf(sc[i][2], sc2, ms1)); sc[i][3] = ex2(fmaf(sc[i][3], sc2, ms1));
                l0 += sc[i][0] + sc[i][1]; l1 += sc[i][2] + sc[i][3];
                pp[i >> 1][(i & 1) * 2] = pack_bf16(sc[i][0], sc[i][1]); pp[i >> 1][(i & 1) * 2 + 1] = pack_bf16(sc[i][2], sc[i][3]);
            }
            pp[2][2] = 0; pp[2][3] = 0;
            l0 += __shfl_xor_sync(~0u, l0, 1); l0 += __shfl_xor_sync(~0u, l0, 2);
            l1 += __shfl_xor_sync(~0u, l1, 1); l1 += __shfl_xor_sync(~0u, l1, 2);
            const float i0 = __fdividef(1.f, l0), i1 = __fdividef(1.f, l1);
            bf16* o0p = g_otok + (size_t)(seg * SEG + tq0) * 4096 + head * 128 + w4 * 32 + 2 * t;
            bf16* o1p = o0p + 2 * 4096;
            #pragma unroll
            for (int nt = 0; nt < 4; nt++) {
                uint32_t vx[4], vm[2];
                const int dim = w4 * 32 + nt * 8 + r8;
                ldsm4(vx, sV + dim * TOKP + mi * 16);
                ldsm2(vm, sVM + dim * 16);
                float c[4] = {}, d[4] = {};
                mma16816(c, pp[0], vm[0], vx[0]);
                mma16816(d, pp[1], vx[1], vx[2]);
                mma16816(c, pp[2], vx[3], 0u);
                *(uint32_t*)(o0p + nt * 8) = pack_bf16((c[0] + d[0]) * i0, (c[1] + d[1]) * i0);
                *(uint32_t*)(o1p + nt * 8) = pack_bf16((c[2] + d[2]) * i1, (c[3] + d[3]) * i1);
            }
        };
        long long t_red = clock64();
        #pragma unroll 1
        for (int s = 0; s < NSEG; s++) {
            const int par = s & 1;
            const int tb = s % 3, tph = (s / 3) & 1;
            TSTAMP(0);
            if (boss) { mbar_expect(barMem, mem_remote_bytes); mbar_expect(barQK, rank == 2 ? 4096 : 2048); mbar_expect(barV, rank == 2 ? 0 : 2048); }
            if (nvalid > 0) {
                float v[12];
                if (s == 0) {
                    #pragma unroll
                    for (int i = 0; i < 3; i++)
                        #pragma unroll
                        for (int hf = 0; hf < 2; hf++) {
                            int f = min((tile0 + i) * 16 + hf * 8 + g, 511);
                            v[i * 4 + hf * 2] = __bfloat162float(mem0[(2 * t) * 512 + f]);
                            v[i * 4 + hf * 2 + 1] = __bfloat162float(mem0[(2 * t + 1) * 512 + f]);
                        }
                } else {
                    const float4* src = &g_acc[s][slot][0][lane];
                    while (clock64() - t_red < POLL_DELAY) {}
                    float4 a, b, c, d;
                    d = make_float4(0.f, 0.f, 0.f, 32.f);
                    #pragma unroll 1
                    for (int it = 0; it < 2000000; it++) {
                        a = ld_relaxed_f4(src); b = ld_relaxed_f4(src + 32); c = ld_relaxed_f4(src + 64);
                        if (nvalid == 3) d = ld_relaxed_f4(src + 96);
                        if (a.w == 32.f && b.w == 32.f && c.w == 32.f && d.w == 32.f) break;
                    }
                    v[0] = a.x; v[1] = a.y; v[2] = a.z; v[3] = b.x; v[4] = b.y; v[5] = b.z;
                    v[6] = c.x; v[7] = c.y; v[8] = c.z; v[9] = d.x; v[10] = d.y; v[11] = d.z;
                }
                TSTAMP(1);
                const uint32_t off0 = CH_MEMT + (tile0 * 16 + g) * 16 + t * 4;
                uint32_t wv[6];
                #pragma unroll
                for (int q = 0; q < 6; q++) wv[q] = pack_bf16(v[2 * q], v[2 * q + 1]);
                #pragma unroll
                for (int q = 0; q < 6; q++) if (q < 4 || nvalid == 3) st_async_b32(pr0 + off0 + q * 128, wv[q], pr0 + CH_BAR);
                #pragma unroll
                for (int q = 0; q < 6; q++) if (q < 4 || nvalid == 3) st_async_b32(pr1 + off0 + q * 128, wv[q], pr1 + CH_BAR);
                #pragma unroll
                for (int q = 0; q < 6; q++) if (q < 4 || nvalid == 3) asm volatile("st.shared.b32 [%0], %1;" :: "r"(sb + off0 + q * 128), "r"(wv[q]) : "memory");
            }
            bar_arrive(1, 384);
            if (rank != 0 && s > 0) tok_attn(s - 1);
            TSTAMP(3);
            if (boss) {
                mbar_wait(barQK, par); mbar_wait(barV, par);
                if (s == 0) issue_x(2);
                if (s + 3 < NSEG) { issue_x(s + 3); }
                mbar_wait(barTok + tb * 8, tph);
                if (s + 3 < NSEG) mbar_expect(barTok + tb * 8, tok_bytes);
            }
            __syncwarp();
            if (s + 1 < NSEG) {
                named_bar(3, 384);
                TSTAMP(6);
                if (nvalid > 0) {
                    float c[6][4] = {};
                    #pragma unroll
                    for (int kk = 0; kk < 8; kk++) {
                        uint2 ob = *(const uint2*)(smem + CH_OB + kk * 256 + lane * 8);
                        #pragma unroll
                        for (int i = 0; i < 3; i++) mma16816(c[i * 2 + (kk & 1)], wr[i * 8 + kk], ob.x, ob.y);
                    }
                    if (s == 0) {
                        if (tid == 256) {
                            for (int it = 0; it < 2000000; it++) {
                                unsigned v; asm volatile("ld.acquire.gpu.global.u32 %0, [%1];" : "=r"(v) : "l"(&g_gridbar) : "memory");
                                if ((int)(v - bar_target) >= 0) break;
                            }
                        }
                    }
                    TSTAMP(13);
                    float o[12];
                    #pragma unroll
                    for (int i = 0; i < 3; i++)
                        #pragma unroll
                        for (int e = 0; e < 4; e++) o[i * 4 + e] = c[2 * i][e] + c[2 * i + 1][e];
                    bar_arrive(6, 384);
                    if (s == 0) named_bar(5, (rank == 2) ? 96 : 128);
                    float4* dst = &g_acc[s + 1][slot][0][lane];
                    red_v4(dst, o[0], o[1], o[2], 1.f);
                    red_v4(dst + 32, o[3], o[4], o[5], 1.f);
                    red_v4(dst + 64, o[6], o[7], o[8], 1.f);
                    if (nvalid == 3) red_v4(dst + 96, o[9], o[10], o[11], 1.f);
                } else {
                    bar_arrive(6, 384);
                }
                t_red = clock64();
                TSTAMP(7);
            }
        }
        if (rank != 0) {
            mbar_wait(barQK, (NSEG - 1) & 1); mbar_wait(barV, (NSEG - 1) & 1);
            mbar_wait(barTok + ((NSEG - 1) % 3) * 8, ((NSEG - 1) / 3) & 1);
            named_bar(7, 128);
            tok_attn(NSEG - 1);
        }
    } else {
        asm volatile("setmaxnreg.inc.sync.aligned.u32 176;");
        uint32_t wr[32][4];
        #pragma unroll
        for (int kk = 0; kk < 32; kk++) {
            int d = kk * 16 + (mi >> 1) * 8 + r8;
            int c = w4 * 2 + (mi & 1);
            ldsm4t(wr[kk], sb + wg * 65536 + d * 128 + ((c ^ (d & 7)) << 4));
        }
        cluster_sync();
        float xacc[16];
        auto xproj = [&](int seg) {
            mbar_wait(barX + (seg & 1) * 8, (seg >> 1) & 1);
            wg_fence();
            #pragma unroll
            for (int kk = 0; kk < 32; kk++) {
                uint64_t desc = make_desc(sb + CH_XS + (seg & 1) * 32768 + (kk >> 2) * 4096 + (kk & 3) * 32, 16, 1024, 1);
                wgmma_rs_n32(xacc, wr[kk], desc, kk > 0);
            }
            wg_commit();
            wg_wait<0>();
            const int buf = seg % 3;
            uint32_t p0[4], p1[4];
            #pragma unroll
            for (int j = 0; j < 4; j++) { p0[j] = pack_bf16(xacc[4 * j], xacc[4 * j + 1]); p1[j] = pack_bf16(xacc[4 * j + 2], xacc[4 * j + 3]); }
            const int e = wg * 64 + w4 * 16 + g;
            {
                const uint32_t a = (rank == 0) ? sb + CH_QX + buf * 12288 + (t >> 1) * 6144 + e * 48 + (t & 1) * 16
                                               : sb + ((rank == 1) ? CH_KX : CH_VX) + buf * 10240 + e * TOKP + t * 16;
                const uint32_t a8 = a + 8 * ((rank == 0) ? 48 : TOKP);
                asm volatile("st.shared.v4.b32 [%0], {%1,%2,%3,%4};" :: "r"(a), "r"(p0[0]), "r"(p0[1]), "r"(p0[2]), "r"(p0[3]) : "memory");
                asm volatile("st.shared.v4.b32 [%0], {%1,%2,%3,%4};" :: "r"(a8), "r"(p1[0]), "r"(p1[1]), "r"(p1[2]), "r"(p1[3]) : "memory");
                asm volatile("fence.proxy.async.shared::cta;" ::: "memory");
            }
        };
        auto tok_bcast = [&](int seg) {
            if (tid == 224) {
                const int buf = seg % 3;
                if (rank != 0) {
                    const uint32_t boff = ((rank == 1) ? CH_KX : CH_VX) + buf * 10240;
                    bulk_s2s(pr0 + boff, sb + boff, 10240, pr0 + CH_BAR + 24 + buf * 8);
                    bulk_s2s(pr1 + boff, sb + boff, 10240, pr1 + CH_BAR + 24 + buf * 8);
                } else {
                    const uint32_t boff = CH_QX + buf * 12288;
                    bulk_s2s(pr0 + boff, sb + boff, 6144, pr0 + CH_BAR + 24 + buf * 8);
                    bulk_s2s(pr1 + boff, sb + boff + 6144, 6144, pr1 + CH_BAR + 24 + buf * 8);
                }
            }
        };
        xproj(0);
        xproj(1);
        named_bar(4, 256);
        tok_bcast(0);
        const float sc2 = 0.08838834764831845f * 1.4426950408889634f;
        const uint32_t memt_lane = sb + CH_MEMT + lane * 16;

        #pragma unroll 1
        for (int s = 0; s < NSEG; s++) {
            const int par = s & 1;
            const int tb = s % 3, tph = (s / 3) & 1;
            TSTAMP(0);
            named_bar(1, 384);
            TSTAMP(1);
            {
                float c[4][4] = {};
                if (rank == 0) {
                    qkv_range<0, 6>(c, wr, memt_lane);
                    mbar_wait(barMem, par); TSTAMP(2);
                    qkv_range<6, 16>(c, wr, memt_lane);
                } else if (rank == 1) {
                    qkv_range<6, 12>(c, wr, memt_lane);
                    mbar_wait(barMem, par); TSTAMP(2);
                    qkv_range<0, 6>(c, wr, memt_lane);
                    qkv_range<12, 16>(c, wr, memt_lane);
                } else {
                    qkv_range<12, 16>(c, wr, memt_lane);
                    mbar_wait(barMem, par); TSTAMP(2);
                    qkv_range<0, 12>(c, wr, memt_lane);
                }
                float r0 = (c[0][0] + c[1][0]) + (c[2][0] + c[3][0]);
                float r1 = (c[0][1] + c[1][1]) + (c[2][1] + c[3][1]);
                float r2 = (c[0][2] + c[1][2]) + (c[2][2] + c[3][2]);
                float r3 = (c[0][3] + c[1][3]) + (c[2][3] + c[3][3]);
                uint32_t w0 = pack_bf16(r0, r1), w1 = pack_bf16(r2, r3);
                TSTAMP(10);
                const int e = wg * 64 + w4 * 16 + g;
                uint32_t off = (rank == 0 ? CH_QM : (rank == 1 ? CH_KM + par * 2048 : CH_VM + par * 2048)) + e * 16 + t * 4;
                uint32_t boff = CH_BAR + (rank == 2 ? 16 : 8);
                st_async_b32(pr0 + off, w0, pr0 + boff);
                st_async_b32(pr0 + off + 128, w1, pr0 + boff);
                st_async_b32(pr1 + off, w0, pr1 + boff);
                st_async_b32(pr1 + off + 128, w1, pr1 + boff);
                asm volatile("st.shared.b32 [%0], %1;" :: "r"(sb + off), "r"(w0) : "memory");
                asm volatile("st.shared.b32 [%0], %1;" :: "r"(sb + off + 128), "r"(w1) : "memory");
                __syncwarp();
                if (lane == 0) mbar_arrive(sb + boff);
            }
            TSTAMP(3);
            mbar_wait(barTok + tb * 8, tph);
            uint32_t kb[4][4];
            if (warp >= 1 && warp < 5) {
                #pragma unroll
                for (int j = 0; j < 4; j++)
                    ldsm4t(kb[j], sb + CH_KX + tb * 10240 + (j * 32 + lane) * TOKP + (warp - 1) * 16);
            }
            mbar_wait(barQK, par);
            TSTAMP(4);
            if (warp < 5) {
                if (warp == 0) {
                    #pragma unroll
                    for (int j = 0; j < 4; j++) ldsm4t(kb[j], sb + CH_KM + par * 2048 + (j * 32 + lane) * 16);
                }
                float c[4][4] = {};
                uint32_t q[4][4];
                #pragma unroll
                for (int j = 0; j < 4; j++) ldsm4t(q[j], sb + CH_QM + (j * 32 + lane) * 16);
                #pragma unroll
                for (int j = 0; j < 4; j++) {
                    uint32_t a0[4] = { q[j][0], q[j][0], q[j][1], q[j][1] };
                    uint32_t a1[4] = { q[j][2], q[j][2], q[j][3], q[j][3] };
                    mma16816(c[(2 * j) & 3], a0, kb[j][0], kb[j][1]);
                    mma16816(c[(2 * j + 1) & 3], a1, kb[j][2], kb[j][3]);
                }
                float2 sv = make_float2((c[0][0] + c[1][0]) + (c[2][0] + c[3][0]), (c[0][1] + c[1][1]) + (c[2][1] + c[3][1]));
                *(float2*)(smem + CH_SB + warp * 256 + lane * 8) = sv;
            }
            named_bar(2, 256);
            uint32_t vx[2][4], vm[2];
            #pragma unroll
            for (int nt = 0; nt < 2; nt++)
                ldsm4(vx[nt], sb + CH_VX + tb * 10240 + (warp * 16 + nt * 8 + (lane & 7)) * TOKP + (lane >> 3) * 16);
            mbar_wait(barV, par);
            ldsm2(vm, sb + CH_VM + par * 2048 + (warp * 16 + (lane & 15)) * 16);
            if (s + 1 < NSEG) tok_bcast(s + 1);
            TSTAMP(5);
            {
                float sv[10];
                #pragma unroll
                for (int i = 0; i < 5; i++) {
                    float2 x = *(const float2*)(smem + CH_SB + i * 256 + lane * 8);
                    sv[2 * i] = x.x; sv[2 * i + 1] = x.y;
                }
                float m = fmaxf(fmaxf(fmaxf(sv[0], sv[1]), fmaxf(sv[2], sv[3])), fmaxf(fmaxf(sv[4], sv[5]), fmaxf(sv[6], sv[7])));
                m = fmaxf(m, fmaxf(sv[8], sv[9]));
                m = fmaxf(m, __shfl_xor_sync(~0u, m, 1));
                m = fmaxf(m, __shfl_xor_sync(~0u, m, 2));
                const float ms = -m * sc2;
                #pragma unroll
                for (int i = 0; i < 10; i++) sv[i] = ex2(fmaf(sv[i], sc2, ms));
                uint32_t pa[3][4];
                pa[0][0] = pack_bf16(sv[0], sv[1]); pa[0][1] = 0; pa[0][2] = pack_bf16(sv[2], sv[3]); pa[0][3] = 0;
                pa[1][0] = pack_bf16(sv[4], sv[5]); pa[1][1] = 0; pa[1][2] = pack_bf16(sv[6], sv[7]); pa[1][3] = 0;
                pa[2][0] = pack_bf16(sv[8], sv[9]); pa[2][1] = 0; pa[2][2] = 0; pa[2][3] = 0;
                TSTAMP(11);
                float c0[2][4] = {}, c1[2][4] = {};
                #pragma unroll
                for (int nt = 0; nt < 2; nt++) {
                    mma16816(c0[nt], pa[0], vm[nt], vx[nt][0]);
                    mma16816(c1[nt], pa[1], vx[nt][1], vx[nt][2]);
                }
                #pragma unroll
                for (int nt = 0; nt < 2; nt++) mma16816(c0[nt], pa[2], vx[nt][3], 0u);
                float l = ((sv[0] + sv[1]) + (sv[2] + sv[3])) + ((sv[4] + sv[5]) + (sv[6] + sv[7])) + (sv[8] + sv[9]);
                l += __shfl_xor_sync(~0u, l, 1);
                l += __shfl_xor_sync(~0u, l, 2);
                const float inv_l = __fdividef(1.f, l);
                uint32_t ow0 = pack_bf16((c0[0][0] + c1[0][0]) * inv_l, (c0[0][1] + c1[0][1]) * inv_l);
                uint32_t ow1 = pack_bf16((c0[1][0] + c1[1][0]) * inv_l, (c0[1][1] + c1[1][1]) * inv_l);
                *(uint2*)(smem + CH_OB + warp * 256 + lane * 8) = make_uint2(ow0, ow1);
            }
            if (s + 1 < NSEG) {
                bar_arrive(3, 384);
                named_bar(6, 384);
                TSTAMP(8);
                if (s + 2 < NSEG) xproj(s + 2);
            }
            TSTAMP(9);
        }
    }
    __syncthreads();
    cluster_sync();
}

constexpr int GM_STAGE_BYTES = 32768;
constexpr int gm_smem(int stages) { return stages * GM_STAGE_BYTES + 1024 + 128; }

__device__ __forceinline__ void wgmma_ss_n128_tb(float* d, uint64_t da, uint64_t db, int scale_d) {
    asm volatile("{\n.reg .pred p;\nsetp.ne.b32 p, %66, 0;\n"
        "wgmma.mma_async.sync.aligned.m64n128k16.f32.bf16.bf16 "
        "{%0,%1,%2,%3,%4,%5,%6,%7,%8,%9,%10,%11,%12,%13,%14,%15,%16,%17,%18,%19,%20,%21,%22,%23,%24,%25,%26,%27,%28,%29,%30,%31,"
        "%32,%33,%34,%35,%36,%37,%38,%39,%40,%41,%42,%43,%44,%45,%46,%47,%48,%49,%50,%51,%52,%53,%54,%55,%56,%57,%58,%59,%60,%61,%62,%63}, "
        "%64, %65, p, 1, 1, 0, 1;\n}"
        : "+f"(d[0]), "+f"(d[1]), "+f"(d[2]), "+f"(d[3]), "+f"(d[4]), "+f"(d[5]), "+f"(d[6]), "+f"(d[7]),
          "+f"(d[8]), "+f"(d[9]), "+f"(d[10]), "+f"(d[11]), "+f"(d[12]), "+f"(d[13]), "+f"(d[14]), "+f"(d[15]),
          "+f"(d[16]), "+f"(d[17]), "+f"(d[18]), "+f"(d[19]), "+f"(d[20]), "+f"(d[21]), "+f"(d[22]), "+f"(d[23]),
          "+f"(d[24]), "+f"(d[25]), "+f"(d[26]), "+f"(d[27]), "+f"(d[28]), "+f"(d[29]), "+f"(d[30]), "+f"(d[31]),
          "+f"(d[32]), "+f"(d[33]), "+f"(d[34]), "+f"(d[35]), "+f"(d[36]), "+f"(d[37]), "+f"(d[38]), "+f"(d[39]),
          "+f"(d[40]), "+f"(d[41]), "+f"(d[42]), "+f"(d[43]), "+f"(d[44]), "+f"(d[45]), "+f"(d[46]), "+f"(d[47]),
          "+f"(d[48]), "+f"(d[49]), "+f"(d[50]), "+f"(d[51]), "+f"(d[52]), "+f"(d[53]), "+f"(d[54]), "+f"(d[55]),
          "+f"(d[56]), "+f"(d[57]), "+f"(d[58]), "+f"(d[59]), "+f"(d[60]), "+f"(d[61]), "+f"(d[62]), "+f"(d[63])
        : "l"(da), "l"(db), "r"(scale_d));
}

template <int MODE, int KSPLIT, int GM_STAGES>
__global__ void __launch_bounds__(288, (GM_STAGES <= 3) ? 2 : 1)
gemm_tma(const __grid_constant__ CUtensorMap tmA, const __grid_constant__ CUtensorMap tmB, bf16* __restrict__ C,
         int K, int ntn, int ldc, int coff) {
    extern __shared__ __align__(1024) uint8_t smem_raw[];
    const uint32_t sb = (smem_u32(smem_raw) + 1023) & ~1023u;
    const uint32_t bar0 = sb + GM_STAGES * GM_STAGE_BYTES;
    const int tid = threadIdx.x, lane = tid & 31, warp = tid >> 5;
    const int ks = (KSPLIT == 2) ? (blockIdx.x & 1) : 0;
    const int tile = blockIdx.x / KSPLIT;
    const int m0 = (tile / ntn) * 128, n0 = (tile % ntn) * 128;
    const int kper = K / KSPLIT, kbase = ks * kper, nk = kper / 64;
    if (tid == 0) {
        for (int i = 0; i < GM_STAGES; i++) { mbar_init(bar0 + i * 8, 1); mbar_init(bar0 + 64 + i * 8, 2); }
        asm volatile("fence.mbarrier_init.release.cluster;" ::: "memory");
    }
    __syncthreads();
    if (warp == 8) {
        if (lane == 0) {
            for (int it = 0; it < nk; it++) {
                const int st = it % GM_STAGES, ph = (it / GM_STAGES) & 1;
                mbar_wait(bar0 + 64 + st * 8, ph ^ 1);
                mbar_expect(bar0 + st * 8, GM_STAGE_BYTES);
                const uint32_t sA = sb + st * GM_STAGE_BYTES, sB = sA + 16384;
                const int k0 = kbase + it * 64;
                tma_load_2d(sA, &tmA, k0, m0, bar0 + st * 8);
                tma_load_2d(sB, &tmB, n0, k0, bar0 + st * 8);
                tma_load_2d(sB + 8192, &tmB, n0 + 64, k0, bar0 + st * 8);
            }
        }
    } else {
        const int wg = warp >> 2, w4 = warp & 3, g = lane >> 2, t = lane & 3;
        float acc[64];
        for (int it = 0; it < nk; it++) {
            const int st = it % GM_STAGES, ph = (it / GM_STAGES) & 1;
            mbar_wait(bar0 + st * 8, ph);
            const uint32_t sA = sb + st * GM_STAGE_BYTES + wg * 8192, sB = sb + st * GM_STAGE_BYTES + 16384;
            wg_fence();
            #pragma unroll
            for (int kk = 0; kk < 4; kk++) {
                uint64_t da = make_desc(sA + kk * 32, 16, 1024, 1);
                uint64_t db = make_desc(sB + kk * 2048, 8192, 1024, 1);
                wgmma_ss_n128_tb(acc, da, db, (it > 0 || kk > 0));
            }
            wg_commit();
            if (it > 0) {
                wg_wait<1>();
                if ((tid & 127) == 0) mbar_arrive(bar0 + 64 + ((it - 1) % GM_STAGES) * 8);
            }
        }
        wg_wait<0>();
        #pragma unroll
        for (int j = 0; j < 64; j++) asm volatile("" : "+f"(acc[j]) :: "memory");
        if (KSPLIT == 2) {
            named_bar(1, 256);
            asm volatile("barrier.cluster.arrive.aligned;\nbarrier.cluster.wait.aligned;" ::: "memory");
            const uint32_t red = mapa(sb, 0) + tid * 16;
            if (ks == 1) {
                #pragma unroll
                for (int j = 0; j < 16; j++)
                    asm volatile("st.shared::cluster.v4.f32 [%0], {%1,%2,%3,%4};" :: "r"(red + j * 4096), "f"(acc[4 * j]), "f"(acc[4 * j + 1]), "f"(acc[4 * j + 2]), "f"(acc[4 * j + 3]) : "memory");
            }
            asm volatile("barrier.cluster.arrive.aligned;\nbarrier.cluster.wait.aligned;" ::: "memory");
            if (ks == 1) return;
            #pragma unroll
            for (int j = 0; j < 16; j++) {
                float4 v;
                asm volatile("ld.shared.v4.f32 {%0,%1,%2,%3}, [%4];" : "=f"(v.x), "=f"(v.y), "=f"(v.z), "=f"(v.w) : "r"(sb + tid * 16 + j * 4096) : "memory");
                acc[4 * j] += v.x; acc[4 * j + 1] += v.y; acc[4 * j + 2] += v.z; acc[4 * j + 3] += v.w;
            }
        }
        named_bar(1, 256);
        const int rl = wg * 64 + w4 * 16 + g;
        if (MODE == 0) {
            #pragma unroll
            for (int j = 0; j < 16; j++) {
                #pragma unroll
                for (int hh = 0; hh < 2; hh++) {
                    const uint32_t v = pack_bf16(acc[4 * j + 2 * hh], acc[4 * j + 2 * hh + 1]);
                    asm volatile("st.shared.b32 [%0], %1;" :: "r"(sb + (j >> 1) * 4096 + (rl + hh * 8) * 32 + (j & 1) * 16 + t * 4), "r"(v) : "memory");
                }
            }
            asm volatile("fence.proxy.async.shared::cta;" ::: "memory");
            named_bar(1, 256);
            if (tid < 8) {
                const int col = n0 + tid * 16, which = col >> 9, h = (col >> 4) & 31;
                bf16* dst = C + ((size_t)(which * NH + h) * S_LEN + m0) * 16;
                asm volatile("cp.async.bulk.global.shared::cta.bulk_group [%0], [%1], 4096;" :: "l"(dst), "r"(sb + tid * 4096) : "memory");
                asm volatile("cp.async.bulk.commit_group;" ::: "memory");
                asm volatile("cp.async.bulk.wait_group 0;" ::: "memory");
            }
        } else {
            #pragma unroll
            for (int j = 0; j < 16; j++) {
                #pragma unroll
                for (int hh = 0; hh < 2; hh++) {
                    const uint32_t v = pack_bf16(acc[4 * j + 2 * hh], acc[4 * j + 2 * hh + 1]);
                    asm volatile("st.shared.b32 [%0], %1;" :: "r"(sb + (rl + hh * 8) * 272 + j * 16 + t * 4), "r"(v) : "memory");
                }
            }
            named_bar(1, 256);
            #pragma unroll
            for (int i = 0; i < 8; i++) {
                const int idx = tid + i * 256, r = idx >> 4, c = idx & 15;
                uint4 v;
                asm volatile("ld.shared.v4.b32 {%0,%1,%2,%3}, [%4];" : "=r"(v.x), "=r"(v.y), "=r"(v.z), "=r"(v.w) : "r"(sb + r * 272 + c * 16) : "memory");
                *(uint4*)(C + (size_t)(m0 + r) * ldc + coff + n0 + c * 8) = v;
            }
        }
    }
    if (KSPLIT == 2 && warp == 8) {
        asm volatile("barrier.cluster.arrive.aligned;\nbarrier.cluster.wait.aligned;" ::: "memory");
        asm volatile("barrier.cluster.arrive.aligned;\nbarrier.cluster.wait.aligned;" ::: "memory");
    }
}

__device__ float g_kmax2[NH];

__global__ void __launch_bounds__(256) knorm_kernel(const bf16* __restrict__ qkv) {
    const int h = blockIdx.x, tid = threadIdx.x;
    const uint4* Kp = (const uint4*)(qkv + (size_t)(1 * NH + h) * S_LEN * 16);
    float mx = 0.f;
    for (int j = tid; j < S_LEN; j += 256) {
        uint4 a = Kp[2 * j], b = Kp[2 * j + 1];
        const uint32_t w[8] = { a.x, a.y, a.z, a.w, b.x, b.y, b.z, b.w };
        float s = 0.f;
        #pragma unroll
        for (int i = 0; i < 8; i++) {
            float lo = __uint_as_float(w[i] << 16), hi = __uint_as_float(w[i] & 0xffff0000u);
            s = fmaf(lo, lo, s); s = fmaf(hi, hi, s);
        }
        mx = fmaxf(mx, s);
    }
    #pragma unroll
    for (int o = 16; o > 0; o >>= 1) mx = fmaxf(mx, __shfl_xor_sync(~0u, mx, o));
    __shared__ float sm[8];
    if ((tid & 31) == 0) sm[tid >> 5] = mx;
    __syncthreads();
    if (tid == 0) {
        float m = sm[0];
        for (int i = 1; i < 8; i++) m = fmaxf(m, sm[i]);
        g_kmax2[h] = m;
    }
}

__device__ __noinline__ void attnA_slow_tile(const bf16* __restrict__ Q, const bf16* __restrict__ Kp, const bf16* __restrict__ Vp,
                                             bf16* __restrict__ o, int q0, int h, int lane) {
    const int g = lane >> 2, t = lane & 3;
    uint32_t qa[4];
    qa[0] = *(const uint32_t*)(Q + (q0 + g) * 16 + 2 * t);
    qa[1] = *(const uint32_t*)(Q + (q0 + g + 8) * 16 + 2 * t);
    qa[2] = *(const uint32_t*)(Q + (q0 + g) * 16 + 8 + 2 * t);
    qa[3] = *(const uint32_t*)(Q + (q0 + g + 8) * 16 + 8 + 2 * t);
    const float sc2 = 0.25f * 1.4426950408889634f;
    float m0 = -INFINITY, m1 = -INFINITY, l0 = 0.f, l1 = 0.f;
    float o0[4] = {}, o1[4] = {};
    const unsigned short* Vs = (const unsigned short*)Vp;
    for (int kb = 0; kb < S_LEN; kb += 16) {
        float s[2][4] = {};
        #pragma unroll
        for (int n = 0; n < 2; n++) {
            uint32_t b0 = *(const uint32_t*)(Kp + (kb + n * 8 + g) * 16 + 2 * t);
            uint32_t b1 = *(const uint32_t*)(Kp + (kb + n * 8 + g) * 16 + 8 + 2 * t);
            mma16816(s[n], qa, b0, b1);
        }
        float mx0 = fmaxf(m0, fmaxf(fmaxf(s[0][0], s[0][1]), fmaxf(s[1][0], s[1][1])));
        float mx1 = fmaxf(m1, fmaxf(fmaxf(s[0][2], s[0][3]), fmaxf(s[1][2], s[1][3])));
        mx0 = fmaxf(mx0, __shfl_xor_sync(~0u, mx0, 1)); mx0 = fmaxf(mx0, __shfl_xor_sync(~0u, mx0, 2));
        mx1 = fmaxf(mx1, __shfl_xor_sync(~0u, mx1, 1)); mx1 = fmaxf(mx1, __shfl_xor_sync(~0u, mx1, 2));
        float a0 = ex2((m0 - mx0) * sc2), a1 = ex2((m1 - mx1) * sc2);
        m0 = mx0; m1 = mx1;
        l0 *= a0; l1 *= a1;
        o0[0] *= a0; o0[1] *= a0; o0[2] *= a1; o0[3] *= a1; o1[0] *= a0; o1[1] *= a0; o1[2] *= a1; o1[3] *= a1;
        float p[8];
        p[0] = ex2((s[0][0] - m0) * sc2); p[1] = ex2((s[0][1] - m0) * sc2); p[2] = ex2((s[0][2] - m1) * sc2); p[3] = ex2((s[0][3] - m1) * sc2);
        p[4] = ex2((s[1][0] - m0) * sc2); p[5] = ex2((s[1][1] - m0) * sc2); p[6] = ex2((s[1][2] - m1) * sc2); p[7] = ex2((s[1][3] - m1) * sc2);
        l0 += p[0] + p[1] + p[4] + p[5]; l1 += p[2] + p[3] + p[6] + p[7];
        uint32_t pa[4] = { pack_bf16(p[0], p[1]), pack_bf16(p[2], p[3]), pack_bf16(p[4], p[5]), pack_bf16(p[6], p[7]) };
        #pragma unroll
        for (int n = 0; n < 2; n++) {
            const int d = n * 8 + g;
            uint32_t b0 = (uint32_t)Vs[(kb + 2 * t) * 16 + d] | ((uint32_t)Vs[(kb + 2 * t + 1) * 16 + d] << 16);
            uint32_t b1 = (uint32_t)Vs[(kb + 8 + 2 * t) * 16 + d] | ((uint32_t)Vs[(kb + 8 + 2 * t + 1) * 16 + d] << 16);
            mma16816(n == 0 ? o0 : o1, pa, b0, b1);
        }
    }
    l0 += __shfl_xor_sync(~0u, l0, 1); l0 += __shfl_xor_sync(~0u, l0, 2);
    l1 += __shfl_xor_sync(~0u, l1, 1); l1 += __shfl_xor_sync(~0u, l1, 2);
    float i0 = 1.f / l0, i1 = 1.f / l1;
    *(uint32_t*)(o + (size_t)(q0 + g) * DM + h * 16 + 2 * t) = pack_bf16(o0[0] * i0, o0[1] * i0);
    *(uint32_t*)(o + (size_t)(q0 + g + 8) * DM + h * 16 + 2 * t) = pack_bf16(o0[2] * i1, o0[3] * i1);
    *(uint32_t*)(o + (size_t)(q0 + g) * DM + h * 16 + 8 + 2 * t) = pack_bf16(o1[0] * i0, o1[1] * i0);
    *(uint32_t*)(o + (size_t)(q0 + g + 8) * DM + h * 16 + 8 + 2 * t) = pack_bf16(o1[2] * i1, o1[3] * i1);
}

#define AT_EXB ex2
#define AT_EXA ex2
#define AT_EXC ex2
#define AT_BATCH
#define AT_CHUNK 128
#define AT_UNROLL 2
constexpr int AT_CH = AT_CHUNK;
constexpr int AT_UNR = AT_UNROLL;
constexpr int AT_STAGES = 3;
__global__ void __launch_bounds__(128) attnA_kernel(const bf16* __restrict__ qkv, bf16* __restrict__ o) {
    __shared__ __align__(128) uint8_t sm[AT_STAGES * AT_CH * 64];
    const int tid = threadIdx.x, lane = tid & 31, warp = tid >> 5;
    const int h = blockIdx.y, q0 = blockIdx.x * 128 + warp * 32;
    const int g = lane >> 2, t = lane & 3;
    const bf16* Q = qkv + (size_t)(0 * NH + h) * S_LEN * 16;
    const bf16* Kp = qkv + (size_t)(1 * NH + h) * S_LEN * 16;
    const bf16* Vp = qkv + (size_t)(2 * NH + h) * S_LEN * 16;
    const uint32_t sb = smem_u32(sm);
    auto load_stage = [&](int c) {
        const uint32_t base = sb + (c % AT_STAGES) * (AT_CH * 64);
        #pragma unroll
        for (int i = 0; i < AT_CH / 64; i++) {
            int idx = tid + i * 128, r = idx >> 1, cc = idx & 1;
            uint32_t off = r * 32 + ((cc ^ ((r >> 2) & 1)) << 4);
            cp_async16(base + off, Kp + (size_t)(c * AT_CH + r) * 16 + cc * 8);
            cp_async16(base + AT_CH * 32 + off, Vp + (size_t)(c * AT_CH + r) * 16 + cc * 8);
        }
        asm volatile("cp.async.commit_group;" ::: "memory");
    };
    load_stage(0);
    load_stage(1);
    const float sc2 = 0.25f * 1.4426950408889634f;
    uint32_t qa[2][4];
    float nb[2][2];
    {
        const float kmax = sqrtf(g_kmax2[h]) * 1.0001f;
        #pragma unroll
        for (int mt = 0; mt < 2; mt++) {
            const int r0 = q0 + mt * 16 + g;
            qa[mt][0] = *(const uint32_t*)(Q + r0 * 16 + 2 * t);
            qa[mt][1] = *(const uint32_t*)(Q + (r0 + 8) * 16 + 2 * t);
            qa[mt][2] = *(const uint32_t*)(Q + r0 * 16 + 8 + 2 * t);
            qa[mt][3] = *(const uint32_t*)(Q + (r0 + 8) * 16 + 8 + 2 * t);
            #pragma unroll
            for (int hh = 0; hh < 2; hh++) {
                float a0 = __uint_as_float(qa[mt][hh] << 16), a1 = __uint_as_float(qa[mt][hh] & 0xffff0000u);
                float a2 = __uint_as_float(qa[mt][2 + hh] << 16), a3 = __uint_as_float(qa[mt][2 + hh] & 0xffff0000u);
                float n2 = a0 * a0 + a1 * a1 + a2 * a2 + a3 * a3;
                n2 += __shfl_xor_sync(~0u, n2, 1); n2 += __shfl_xor_sync(~0u, n2, 2);
                nb[mt][hh] = -(sqrtf(n2) * 1.0001f * kmax) * sc2;
            }
        }
    }
    float oa[2][3][4] = {};
    const uint32_t ones = 0x3F803F80u;
    const int rk = (lane & 7) + ((lane >> 4) << 3), ck = (lane >> 3) & 1;
    const uint32_t koff = rk * 32 + ((ck ^ ((rk >> 2) & 1)) << 4);
    const int rv = lane & 15, cv = lane >> 4;
    const uint32_t voff = AT_CH * 32 + rv * 32 + ((cv ^ ((rv >> 2) & 1)) << 4);
    constexpr int NCH = S_LEN / AT_CH;
    #pragma unroll 1
    for (int c = 0; c < NCH; c++) {
        asm volatile("cp.async.wait_group 1;" ::: "memory");
        __syncthreads();
        if (c + 2 < NCH) load_stage(c + 2); else asm volatile("cp.async.commit_group;" ::: "memory");
        const uint32_t base = sb + (c % AT_STAGES) * (AT_CH * 64);
        #pragma unroll AT_UNR
        for (int j = 0; j < AT_CH / 16; j++) {
            uint32_t kb[4], vb[4];
            ldsm4(kb, base + j * 512 + koff);
            ldsm4t(vb, base + j * 512 + voff);
            float sA[2][2][4] = {};
            #pragma unroll
            for (int mt = 0; mt < 2; mt++) { mma16816(sA[mt][0], qa[mt], kb[0], kb[1]); mma16816(sA[mt][1], qa[mt], kb[2], kb[3]); }
            uint32_t pa2[2][4];
            #pragma unroll
            for (int mt = 0; mt < 2; mt++) {
                #pragma unroll
                for (int n = 0; n < 2; n++) {
                    pa2[mt][2 * n] = pack_bf16_trunc(ex2(fmaf(sA[mt][n][0], sc2, nb[mt][0])), ex2(fmaf(sA[mt][n][1], sc2, nb[mt][0])));
                    pa2[mt][2 * n + 1] = pack_bf16_trunc(ex2(fmaf(sA[mt][n][2], sc2, nb[mt][1])), ex2(fmaf(sA[mt][n][3], sc2, nb[mt][1])));
                }
            }
            #pragma unroll
            for (int mt = 0; mt < 2; mt++) {
                mma16816(oa[mt][0], pa2[mt], vb[0], vb[1]);
                mma16816(oa[mt][1], pa2[mt], vb[2], vb[3]);
                mma16816(oa[mt][2], pa2[mt], ones, ones);
            }
        }
    }
    #pragma unroll
    for (int mt = 0; mt < 2; mt++) {
        const float l0 = oa[mt][2][0], l1 = oa[mt][2][2];
        const bool bad = !(l0 > 1e-27f && l1 > 1e-27f && l0 < 1e30f && l1 < 1e30f);
        if (__any_sync(~0u, bad)) {
            attnA_slow_tile(Q, Kp, Vp, o, q0 + mt * 16, h, lane);
        } else {
            const float i0 = 1.f / l0, i1 = 1.f / l1;
            const int r0 = q0 + mt * 16 + g;
            *(uint32_t*)(o + (size_t)r0 * DM + h * 16 + 2 * t) = pack_bf16(oa[mt][0][0] * i0, oa[mt][0][1] * i0);
            *(uint32_t*)(o + (size_t)(r0 + 8) * DM + h * 16 + 2 * t) = pack_bf16(oa[mt][0][2] * i1, oa[mt][0][3] * i1);
            *(uint32_t*)(o + (size_t)r0 * DM + h * 16 + 8 + 2 * t) = pack_bf16(oa[mt][1][0] * i0, oa[mt][1][1] * i0);
            *(uint32_t*)(o + (size_t)(r0 + 8) * DM + h * 16 + 8 + 2 * t) = pack_bf16(oa[mt][1][2] * i1, oa[mt][1][3] * i1);
        }
    }
}

typedef CUresult (*PFN_encodeTiled)(CUtensorMap*, CUtensorMapDataType, cuuint32_t, void*, const cuuint64_t*, const cuuint64_t*,
                                    const cuuint32_t*, const cuuint32_t*, CUtensorMapInterleave, CUtensorMapSwizzle,
                                    CUtensorMapL2promotion, CUtensorMapFloatOOBfill);

static CUtensorMap make_tmap_2d(PFN_encodeTiled enc, const void* ptr, uint64_t inner, uint64_t outer, uint32_t box_inner, uint32_t box_outer) {
    CUtensorMap tm;
    cuuint64_t dims[2] = { inner, outer };
    cuuint64_t strides[1] = { inner * 2 };
    cuuint32_t box[2] = { box_inner, box_outer };
    cuuint32_t es[2] = { 1, 1 };
    enc(&tm, CU_TENSOR_MAP_DATA_TYPE_BFLOAT16, 2, (void*)ptr, dims, strides, box, es, CU_TENSOR_MAP_INTERLEAVE_NONE,
        CU_TENSOR_MAP_SWIZZLE_128B, CU_TENSOR_MAP_L2_PROMOTION_L2_128B, CU_TENSOR_MAP_FLOAT_OOB_FILL_NONE);
    return tm;
}

#define TL(i, strm) do {} while (0)
extern "C" void kernel_launch(void* const* d_in, const int* in_sizes, int n_in, void* d_out, int out_size) {
    const bf16* A_x = (const bf16*)d_in[0];
    const bf16* A_wqkv = (const bf16*)d_in[1];
    const bf16* A_wo = (const bf16*)d_in[2];
    const bf16* B_x = (const bf16*)d_in[3];
    const bf16* B_mem0 = (const bf16*)d_in[4];
    const bf16* B_Wq = (const bf16*)d_in[5];
    const bf16* B_Wk = (const bf16*)d_in[6];
    const bf16* B_Wv = (const bf16*)d_in[7];
    const bf16* B_Wo = (const bf16*)d_in[8];
    bf16* out = (bf16*)d_out;

    static PFN_encodeTiled enc = nullptr;
    static CUtensorMap tmX, tmAx, tmWqkv, tmOA, tmWoA, tmOtok, tmWoB;
    static const void* key[5] = { nullptr, nullptr, nullptr, nullptr, nullptr };
    static bf16 *p_otok, *p_qkvA, *p_oA;
    static cudaStream_t s2;
    static cudaEvent_t evFork, evJoin;
    if (!enc) {
        int prLo = 0, prHi = 0;
        cudaDeviceGetStreamPriorityRange(&prLo, &prHi);
        cudaStreamCreateWithPriority(&s2, cudaStreamNonBlocking, prLo);
        cudaEventCreateWithFlags(&evFork, cudaEventDisableTiming);
        cudaEventCreateWithFlags(&evJoin, cudaEventDisableTiming);
        void* fn = nullptr; cudaDriverEntryPointQueryResult qres;
        cudaGetDriverEntryPoint("cuTensorMapEncodeTiled", &fn, cudaEnableDefault, &qres);
        enc = (PFN_encodeTiled)fn;
        cudaFuncSetAttribute(chain_kernel, cudaFuncAttributeMaxDynamicSharedMemorySize, CH_SMEM_ALLOC);
        cudaFuncSetAttribute(gemm_tma<0, 1, 3>, cudaFuncAttributeMaxDynamicSharedMemorySize, gm_smem(3));
        cudaFuncSetAttribute(gemm_tma<1, 1, 3>, cudaFuncAttributeMaxDynamicSharedMemorySize, gm_smem(3));
        cudaFuncSetAttribute(gemm_tma<1, 2, 6>, cudaFuncAttributeMaxDynamicSharedMemorySize, gm_smem(6));
        cudaGetSymbolAddress((void**)&p_otok, g_otok);
        cudaGetSymbolAddress((void**)&p_qkvA, g_qkvA);
        cudaGetSymbolAddress((void**)&p_oA, g_oA);
        tmOA = make_tmap_2d(enc, p_oA, 512, 2048, 64, 128);
        tmOtok = make_tmap_2d(enc, p_otok, 4096, 2048, 64, 128);
    }
    if (key[0] != (const void*)B_x || key[1] != (const void*)A_x || key[2] != (const void*)A_wqkv || key[3] != (const void*)B_Wo || key[4] != (const void*)A_wo) {
        tmX = make_tmap_2d(enc, B_x, 512, 2048, 64, 32);
        tmAx = make_tmap_2d(enc, A_x, 512, 2048, 64, 128);
        tmWqkv = make_tmap_2d(enc, A_wqkv, 1536, 512, 64, 64);
        tmWoA = make_tmap_2d(enc, A_wo, 512, 512, 64, 64);
        tmWoB = make_tmap_2d(enc, B_Wo, 512, 4096, 64, 64);
        key[0] = B_x; key[1] = A_x; key[2] = A_wqkv; key[3] = B_Wo; key[4] = A_wo;
    }

    cudaStream_t st = cudaStreamPerThread;
    TL(0, st);
    cudaEventRecord(evFork, st);
    cudaStreamWaitEvent(s2, evFork, 0);
    chain_kernel<<<96, 384, CH_SMEM_ALLOC, st>>>(tmX, B_mem0, B_Wq, B_Wk, B_Wv, B_Wo);
    TL(1, st);
    gemm_tma<0, 1, 3><<<16 * 12, 288, gm_smem(3), s2>>>(tmAx, tmWqkv, p_qkvA, 512, 12, 0, 0);
    TL(2, s2);
    knorm_kernel<<<NH, 256, 0, s2>>>(p_qkvA);
    attnA_kernel<<<dim3(2048 / 128, NH), 128, 0, s2>>>(p_qkvA, p_oA);
    TL(3, s2);
    gemm_tma<1, 1, 3><<<16 * 4, 288, gm_smem(3), s2>>>(tmOA, tmWoA, out, 512, 4, 1024, 0);
    TL(4, s2);
    cudaEventRecord(evJoin, s2);
    {
        cudaLaunchConfig_t cfg = {};
        cfg.gridDim = dim3(16 * 4 * 2); cfg.blockDim = dim3(288); cfg.dynamicSmemBytes = gm_smem(6); cfg.stream = st;
        cudaLaunchAttribute at[1]; at[0].id = cudaLaunchAttributeClusterDimension; at[0].val.clusterDim.x = 2; at[0].val.clusterDim.y = 1; at[0].val.clusterDim.z = 1;
        cfg.attrs = at; cfg.numAttrs = 1;
        cudaLaunchKernelEx(&cfg, gemm_tma<1, 2, 6>, tmOtok, tmWoB, out, 4096, 4, 1024, 512);
    }
    TL(6, st);
    cudaStreamWaitEvent(st, evJoin, 0);
    TL(7, st);
}
```
